```python
import torch

def _softmax(x, axis=-1):
    return torch.softmax(x, dim=axis)

def _gelu(x):
    return torch.nn.functional.gelu(x, approximate='tanh')

def _silu(x):
    return torch.nn.functional.silu(x)

def _sigmoid(x):
    return torch.sigmoid(x)

def _layernorm(x, axis=-1, eps=1e-05):
    m = x.mean(dim=axis, keepdim=True)
    v = x.var(dim=axis, keepdim=True, unbiased=False)
    return (x - m) / torch.sqrt(v + eps)

def _scatter_add(tgt, idx, src, axis=0):
    return tgt.clone().index_add_(axis, idx, src)

def _segment_sum(src, seg, n):
    out = torch.zeros((n,) + src.shape[1:], dtype=src.dtype)
    return out.index_add_(0, seg, src)

def _pad(x, pw):
    flat = tuple((v for pair in reversed(pw) for v in pair))
    return torch.nn.functional.pad(x, flat)
kernel_name = 'standalone__kv_cache_quant_pre_rope_vs_post_rope__decode'

def setup_inputs():

    _w = lambda a: (lambda t: t.to(torch.bfloat16) if t.is_floating_point() else t)(torch.as_tensor(a))
    B, Sq, Skv = (1, 1, 8192)
    H, Dh0 = (32, 128)
    G = 64 if 64 > 0 else Dh0
    G = max(2, G // 2 * 2)
    Dh = max(G, Dh0 // G * G)
    Skv = max(Skv, Sq)
    ng = Dh // G
    bits = 4 if 4 > 1 else 4
    bits = max(2, min(8, bits))
    qmax = (1 << bits) - 1
    half = Dh // 2
    inv = 1.0 / 10000.0 ** (torch.arange(half) / max(1, half))
    ang_k = torch.arange(Skv)[:, None] * inv[None, :]
    ang_q = torch.arange(Skv - Sq, Skv)[:, None] * inv[None, :]
    kc = torch.cat([torch.cos(ang_k), torch.cos(ang_k)], dim=-1)
    ks = torch.cat([torch.sin(ang_k), torch.sin(ang_k)], dim=-1)
    qc = torch.cat([torch.cos(ang_q), torch.cos(ang_q)], dim=-1)
    qs = torch.cat([torch.sin(ang_q), torch.sin(ang_q)], dim=-1)
    qk_i = torch.randint(0, qmax + 1, (B, H, Skv, Dh)).to(torch.int32)
    qv_i = torch.randint(0, qmax + 1, (B, H, Skv, Dh)).to(torch.int32)
    ksc = torch.abs((lambda *s: torch.randn(*s, dtype=torch.bfloat16) * 0.2)(B, H, Skv, ng)) * 0.1 + 0.01
    kzp = torch.full((B, H, Skv, ng), qmax / 2.0)
    vsc = torch.abs((lambda *s: torch.randn(*s, dtype=torch.bfloat16) * 0.2)(B, H, Skv, ng)) * 0.1 + 0.01
    vzp = torch.full((B, H, Skv, ng), qmax / 2.0)
    return {'q': _w((lambda *s: torch.randn(*s, dtype=torch.bfloat16) * 6.4)(B, H, Sq, Dh) * 0.5), 'qk': _w(qk_i), 'k_scales': _w(ksc), 'k_zeros': _w(kzp), 'qv': _w(qv_i), 'v_scales': _w(vsc), 'v_zeros': _w(vzp), 'q_cos': _w(qc), 'q_sin': _w(qs), 'k_cos': _w(kc), 'k_sin': _w(ks)}

def reference(q, qk, k_scales, k_zeros, qv, v_scales, v_zeros, q_cos, q_sin, k_cos, k_sin):
    B, H, Sq, Dh = q.shape
    ng = k_scales.shape[-1]
    G = Dh // ng
    half = Dh // 2
    ks = (lambda x, n, axis: torch.repeat_interleave(x, n, dim=axis))(k_scales, G, axis=-1)
    kz = (lambda x, n, axis: torch.repeat_interleave(x, n, dim=axis))(k_zeros, G, axis=-1)
    k = ((lambda x, dt: x.to(dt))(qk, q.dtype) - kz) * ks
    vs = (lambda x, n, axis: torch.repeat_interleave(x, n, dim=axis))(v_scales, G, axis=-1)
    vz = (lambda x, n, axis: torch.repeat_interleave(x, n, dim=axis))(v_zeros, G, axis=-1)
    v = ((lambda x, dt: x.to(dt))(qv, q.dtype) - vz) * vs
    k1 = k[..., :half].clone()
    k2 = k[..., half:].clone()
    krh = torch.concatenate([-k2, k1], axis=-1)
    kr = k * k_cos[None, None, :, :] + krh * k_sin[None, None, :, :]
    q1 = q[..., :half].clone()
    q2 = q[..., half:].clone()
    qrh = torch.concatenate([-q2, q1], axis=-1)
    qr = q * q_cos[None, None, :, :] + qrh * q_sin[None, None, :, :]
    logits = torch.einsum('bhqd,bhkd->bhqk', qr, kr) * float(Dh) ** (-0.5)
    attn = _softmax(logits, axis=-1)
    out = torch.einsum('bhqk,bhkd->bhqd', attn, v)
    return out
```

```cpp
#include <cuda_runtime.h>
#include <cuda_bf16.h>
#include <stdint.h>

#define KP 32
#define KNST 4
#define NCW 8
#define NTHREADS (NCW * 32 + 32)

namespace {

constexpr int H = 32, S = 8192, D = 128;
constexpr int P = KP, NST = KNST;
constexpr int BPH = S / P;
constexpr int NITEMS = BPH * H;
constexpr int RPW = P / NCW;
constexpr int MAXCTA = 160;

constexpr uint32_t KV_BYTES = P * D * 4;
constexpr uint32_t CS_BYTES = P * D * 2;
constexpr uint32_t SC_BYTES = P * 4;
constexpr uint32_t OFF_K = 0, OFF_V = KV_BYTES, OFF_C = 2 * KV_BYTES, OFF_S = OFF_C + CS_BYTES;
constexpr uint32_t OFF_KS = OFF_S + CS_BYTES, OFF_KZ = OFF_KS + SC_BYTES, OFF_VS = OFF_KZ + SC_BYTES,
                   OFF_VZ = OFF_VS + SC_BYTES;
constexpr uint32_t SLOT_TX = OFF_VZ + SC_BYTES;
constexpr uint32_t SLOT = (SLOT_TX + 127) / 128 * 128;
constexpr uint32_t OFF_Q = NST * SLOT;
constexpr uint32_t OFF_RED = OFF_Q + H * D * 4;
constexpr uint32_t RED_STRIDE = D + 4;
constexpr uint32_t SMEM_BYTES = OFF_RED + 2 * NCW * RED_STRIDE * 4;

constexpr int PART_STRIDE = D + 4;
__device__ float g_part[H * MAXCTA * PART_STRIDE];
__device__ unsigned int g_ticket;
__device__ unsigned int g_done;
__device__ unsigned int g_exit;

__device__ __forceinline__ uint32_t smem_u32(const void* p) { return (uint32_t)__cvta_generic_to_shared(p); }
__device__ __forceinline__ void mbar_init(uint32_t bar, uint32_t cnt) {
    asm volatile("mbarrier.init.shared.b64 [%0], %1;" ::"r"(bar), "r"(cnt) : "memory");
}
__device__ __forceinline__ void mbar_expect_tx(uint32_t bar, uint32_t bytes) {
    asm volatile("mbarrier.arrive.expect_tx.shared.b64 _, [%0], %1;" ::"r"(bar), "r"(bytes) : "memory");
}
__device__ __forceinline__ void mbar_arrive(uint32_t bar) {
    asm volatile("mbarrier.arrive.shared.b64 _, [%0];" ::"r"(bar) : "memory");
}
__device__ __forceinline__ void mbar_wait(uint32_t bar, uint32_t parity) {
    uint32_t done;
    int it = 0;
    do {
        asm volatile("{ .reg .pred p; mbarrier.try_wait.parity.shared.b64 p, [%1], %2; selp.u32 %0, 1, 0, p; }"
                     : "=r"(done) : "r"(bar), "r"(parity) : "memory");
        if (++it > (1 << 24)) __trap();
    } while (!done);
}
__device__ __forceinline__ void bulk_g2s(uint32_t dst, const void* src, uint32_t bytes, uint32_t bar) {
    asm volatile("cp.async.bulk.shared::cluster.global.mbarrier::complete_tx::bytes [%0], [%1], %2, [%3];"
                 ::"r"(dst), "l"(src), "r"(bytes), "r"(bar) : "memory");
}
__device__ __forceinline__ void bulk_g2s_hint(uint32_t dst, const void* src, uint32_t bytes, uint32_t bar, uint64_t pol) {
    asm volatile("cp.async.bulk.shared::cluster.global.mbarrier::complete_tx::bytes.L2::cache_hint [%0], [%1], %2, [%3], %4;"
                 ::"r"(dst), "l"(src), "r"(bytes), "r"(bar), "l"(pol) : "memory");
}
__device__ __forceinline__ int4 lds128(uint32_t a) {
    int4 v;
    asm volatile("ld.shared.v4.s32 {%0,%1,%2,%3}, [%4];" : "=r"(v.x), "=r"(v.y), "=r"(v.z), "=r"(v.w) : "r"(a));
    return v;
}
__device__ __forceinline__ uint2 lds64(uint32_t a) {
    uint2 v;
    asm volatile("ld.shared.v2.u32 {%0,%1}, [%2];" : "=r"(v.x), "=r"(v.y) : "r"(a));
    return v;
}
__device__ __forceinline__ uint32_t lds32(uint32_t a) {
    uint32_t v;
    asm volatile("ld.shared.u32 %0, [%1];" : "=r"(v) : "r"(a));
    return v;
}
__device__ __forceinline__ uint32_t lds16(uint32_t a) {
    uint16_t v;
    asm volatile("ld.shared.u16 %0, [%1];" : "=h"(v) : "r"(a));
    return v;
}
__device__ __forceinline__ uint32_t bf2_mul(uint32_t a, uint32_t b) {
    uint32_t d; asm("mul.rn.bf16x2 %0, %1, %2;" : "=r"(d) : "r"(a), "r"(b)); return d;
}
__device__ __forceinline__ uint32_t bf2_add(uint32_t a, uint32_t b) {
    uint32_t d; asm("add.rn.bf16x2 %0, %1, %2;" : "=r"(d) : "r"(a), "r"(b)); return d;
}
__device__ __forceinline__ uint32_t bf2_sub(uint32_t a, uint32_t b) {
    uint32_t d; asm("sub.rn.bf16x2 %0, %1, %2;" : "=r"(d) : "r"(a), "r"(b)); return d;
}
__device__ __forceinline__ uint32_t bf2_pack(float lo, float hi) {
    uint32_t d; asm("cvt.rn.bf16x2.f32 %0, %1, %2;" : "=r"(d) : "f"(hi), "f"(lo)); return d;
}
__device__ __forceinline__ float bf_lo(uint32_t v) { return __uint_as_float(v << 16); }
__device__ __forceinline__ float bf_hi(uint32_t v) { return __uint_as_float(v & 0xffff0000u); }
__device__ __forceinline__ float bf_round(float x) { return __bfloat162float(__float2bfloat16_rn(x)); }
__device__ __forceinline__ float ex2(float x) { float y; asm("ex2.approx.ftz.f32 %0, %1;" : "=f"(y) : "f"(x)); return y; }

constexpr float LOG2E = 1.4426950408889634f;
constexpr float NEG_INF = -__builtin_huge_valf();

__device__ __forceinline__ float exp_diff(float a, float b) {
    return (a == NEG_INF) ? 0.f : ex2((a - b) * LOG2E);
}

__global__ void __launch_bounds__(NTHREADS, 1)
kv_decode_kernel(const __nv_bfloat16* __restrict__ q, const int* __restrict__ qk,
                 const __nv_bfloat16* __restrict__ ks, const __nv_bfloat16* __restrict__ kz,
                 const int* __restrict__ qv, const __nv_bfloat16* __restrict__ vs,
                 const __nv_bfloat16* __restrict__ vz, const __nv_bfloat16* __restrict__ q_cos,
                 const __nv_bfloat16* __restrict__ q_sin, const __nv_bfloat16* __restrict__ k_cos,
                 const __nv_bfloat16* __restrict__ k_sin, __nv_bfloat16* __restrict__ out) {
    extern __shared__ __align__(128) unsigned char smem[];
    __shared__ __align__(8) uint64_t s_full[NST], s_empty[NST];
    __shared__ volatile int s_item[NST];
    const int warp = threadIdx.x >> 5, lane = threadIdx.x & 31;
    const uint32_t sbase = smem_u32(smem);
    const int nct = gridDim.x;

    if (warp == NCW) {
        if (lane == 0) {
            for (int s = 0; s < NST; s++) { mbar_init(smem_u32(&s_full[s]), 1); mbar_init(smem_u32(&s_empty[s]), NCW); }
            asm volatile("fence.mbarrier_init.release.cluster;" ::: "memory");
        }
        __syncwarp();
        uint64_t pol;
        asm volatile("createpolicy.fractional.L2::evict_first.b64 %0, 1.0;" : "=l"(pol));
        const unsigned char* src = nullptr; uint32_t dsto = 0, bytes = 0, mul = 0; bool tab = false;
        switch (lane) {
            case 0: src = (const unsigned char*)qk; dsto = OFF_K; bytes = KV_BYTES; break;
            case 1: src = (const unsigned char*)k_cos; dsto = OFF_C; bytes = CS_BYTES; tab = true; break;
            case 2: src = (const unsigned char*)k_sin; dsto = OFF_S; bytes = CS_BYTES; tab = true; break;
            case 3: src = (const unsigned char*)ks; dsto = OFF_KS; bytes = SC_BYTES; break;
            case 4: src = (const unsigned char*)kz; dsto = OFF_KZ; bytes = SC_BYTES; break;
            case 5: src = (const unsigned char*)qv; dsto = OFF_V; bytes = KV_BYTES; break;
            case 6: src = (const unsigned char*)vs; dsto = OFF_VS; bytes = SC_BYTES; break;
            case 7: src = (const unsigned char*)vz; dsto = OFF_VZ; bytes = SC_BYTES; break;
            default: break;
        }
        mul = bytes;
        int s = 0, ph = 1, cnt = 0;
        uint32_t item = blockIdx.x;
        bool synced = false;
        while (item < (uint32_t)NITEMS) {
            if (cnt >= NST) mbar_wait(smem_u32(&s_empty[s]), ph);
            cnt++;
            uint32_t nxt = item + nct;
            if (cnt >= NST && lane == 0) nxt = NST * nct + atomicAdd(&g_ticket, 1);
            const uint32_t bar = smem_u32(&s_full[s]);
            if (lane == 0) { s_item[s] = item; mbar_expect_tx(bar, SLOT_TX); }
            __syncwarp();
            if (lane < 8) {
                const uint32_t idx = tab ? (item % BPH) : item;
                const unsigned char* g = src + (size_t)idx * mul;
                if (tab) bulk_g2s(sbase + s * SLOT + dsto, g, bytes, bar);
                else bulk_g2s_hint(sbase + s * SLOT + dsto, g, bytes, bar, pol);
            }
            if (cnt == NST) { __syncthreads(); synced = true; }
            if (++s == NST) { s = 0; ph ^= 1; }
            item = __shfl_sync(0xffffffffu, nxt, 0);
        }
        if (!synced) __syncthreads();
        mbar_wait(smem_u32(&s_empty[s]), ph);
        if (lane == 0) { s_item[s] = -1; mbar_arrive(smem_u32(&s_full[s])); }
    } else {
        float* sq = reinterpret_cast<float*>(smem + OFF_Q);
        for (int i = threadIdx.x; i < H * D; i += NCW * 32) {
            const int d = i & (D - 1);
            const float x = __bfloat162float(q[i]);
            const float y = __bfloat162float(q[i ^ 64]);
            const float rh = d < 64 ? -y : y;
            const float t1 = bf_round(x * __bfloat162float(q_cos[d]));
            const float t2 = bf_round(rh * __bfloat162float(q_sin[d]));
            sq[i] = bf_round(t1 + t2);
        }
        __syncthreads();

        const int hw = lane >> 4, li = lane & 15;
        float m = NEG_INF, lsum = 0.f, zsum = 0.f;
        float acc0 = 0.f, acc1 = 0.f, acc2 = 0.f, acc3 = 0.f;
        float4 qlo = make_float4(0, 0, 0, 0), qhi = qlo;
        int cur = -1, nflush = 0;
        float* gp = g_part + (size_t)blockIdx.x * PART_STRIDE;

        int s = 0, ph = 0;
        while (true) {
            mbar_wait(smem_u32(&s_full[s]), ph);
            const int item = s_item[s];
            const int h = item < 0 ? H : item / BPH;
            if (h != cur) {
                if (cur >= 0) {
                    float* red = reinterpret_cast<float*>(smem + OFF_RED) + (nflush & 1) * NCW * RED_STRIDE;
                    float l = lsum + __shfl_xor_sync(0xffffffffu, lsum, 8);
                    l += __shfl_xor_sync(0xffffffffu, l, 16);
                    float z = zsum + __shfl_xor_sync(0xffffffffu, zsum, 8);
                    z += __shfl_xor_sync(0xffffffffu, z, 16);
                    z = __shfl_sync(0xffffffffu, z, hw);
                    *reinterpret_cast<float4*>(red + warp * RED_STRIDE + 4 * lane) =
                        make_float4(acc0 - z, acc1 - z, acc2 - z, acc3 - z);
                    if (lane == 0) { red[warp * RED_STRIDE + D] = m; red[warp * RED_STRIDE + D + 1] = l; }
                    asm volatile("bar.sync 1, %0;" ::"n"(NCW * 32) : "memory");
                    if (warp == (nflush & (NCW - 1))) {
                        float mw[NCW], M = NEG_INF;
#pragma unroll
                        for (int w = 0; w < NCW; w++) { mw[w] = red[w * RED_STRIDE + D]; M = fmaxf(M, mw[w]); }
                        float4 a = make_float4(0, 0, 0, 0); float L = 0.f;
#pragma unroll
                        for (int w = 0; w < NCW; w++) {
                            const float e = exp_diff(mw[w], M);
                            const float4 t = *reinterpret_cast<const float4*>(red + w * RED_STRIDE + 4 * lane);
                            a.x += e * t.x; a.y += e * t.y; a.z += e * t.z; a.w += e * t.w;
                            L += e * red[w * RED_STRIDE + D + 1];
                        }
                        float* dst = gp + (size_t)cur * MAXCTA * PART_STRIDE;
                        *reinterpret_cast<float4*>(dst + 4 * lane) = a;
                        if (lane == 0) *reinterpret_cast<float2*>(dst + D) = make_float2(M, L);
                    }
                    nflush++;
                }
                if (warp == 0) {
                    for (int e = cur + 1; e < h; e++) {
                        float* dst = gp + (size_t)e * MAXCTA * PART_STRIDE;
                        *reinterpret_cast<float4*>(dst + 4 * lane) = make_float4(0, 0, 0, 0);
                        if (lane == 0) *reinterpret_cast<float2*>(dst + D) = make_float2(NEG_INF, 0.f);
                    }
                }
                if (item < 0) break;
                cur = h;
                m = NEG_INF; lsum = 0.f; zsum = 0.f; acc0 = acc1 = acc2 = acc3 = 0.f;
                qlo = *reinterpret_cast<const float4*>(sq + h * D + 4 * li);
                qhi = *reinterpret_cast<const float4*>(sq + h * D + 64 + 4 * li);
            }
            const uint32_t slot = sbase + s * SLOT;
#pragma unroll
            for (int r4 = 0; r4 < RPW; r4 += 4) {
                const int row0 = warp * RPW + r4;
                float dot[2];
#pragma unroll
                for (int it = 0; it < 2; it++) {
                    const int row = row0 + 2 * hw + it;
                    const int4 a = lds128(slot + OFF_K + row * 512 + li * 16);
                    const int4 b = lds128(slot + OFF_K + row * 512 + 256 + li * 16);
                    const uint2 cl = lds64(slot + OFF_C + row * 256 + li * 8);
                    const uint2 ch = lds64(slot + OFF_C + row * 256 + 128 + li * 8);
                    const uint2 sl = lds64(slot + OFF_S + row * 256 + li * 8);
                    const uint2 sh = lds64(slot + OFF_S + row * 256 + 128 + li * 8);
                    const uint32_t sc = lds32(slot + OFF_KS + row * 4);
                    const uint32_t zc = lds32(slot + OFF_KZ + row * 4);
                    const uint32_t s0 = __byte_perm(sc, 0, 0x1010), s1 = __byte_perm(sc, 0, 0x3232);
                    const uint32_t z0 = __byte_perm(zc, 0, 0x1010), z1 = __byte_perm(zc, 0, 0x3232);
                    const uint32_t l0 = bf2_mul(bf2_sub(bf2_pack((float)a.x, (float)a.y), z0), s0);
                    const uint32_t l1 = bf2_mul(bf2_sub(bf2_pack((float)a.z, (float)a.w), z0), s0);
                    const uint32_t h0 = bf2_mul(bf2_sub(bf2_pack((float)b.x, (float)b.y), z1), s1);
                    const uint32_t h1 = bf2_mul(bf2_sub(bf2_pack((float)b.z, (float)b.w), z1), s1);
                    const uint32_t rl0 = bf2_sub(bf2_mul(l0, cl.x), bf2_mul(h0, sl.x));
                    const uint32_t rl1 = bf2_sub(bf2_mul(l1, cl.y), bf2_mul(h1, sl.y));
                    const uint32_t rh0 = bf2_add(bf2_mul(h0, ch.x), bf2_mul(l0, sh.x));
                    const uint32_t rh1 = bf2_add(bf2_mul(h1, ch.y), bf2_mul(l1, sh.y));
                    float d0 = qlo.x * bf_lo(rl0), d1 = qhi.x * bf_lo(rh0);
                    d0 = fmaf(qlo.y, bf_hi(rl0), d0); d1 = fmaf(qhi.y, bf_hi(rh0), d1);
                    d0 = fmaf(qlo.z, bf_lo(rl1), d0); d1 = fmaf(qhi.z, bf_lo(rh1), d1);
                    d0 = fmaf(qlo.w, bf_hi(rl1), d0); d1 = fmaf(qhi.w, bf_hi(rh1), d1);
                    dot[it] = d0 + d1;
                }
                const bool up = lane & 8;
                float t = (up ? dot[1] : dot[0]) + __shfl_xor_sync(0xffffffffu, up ? dot[0] : dot[1], 8);
                t += __shfl_xor_sync(0xffffffffu, t, 4);
                t += __shfl_xor_sync(0xffffffffu, t, 2);
                t += __shfl_xor_sync(0xffffffffu, t, 1);
                const float lg = bf_round(bf_round(t) * 0.08838834764831845f);
                float mx = fmaxf(lg, __shfl_xor_sync(0xffffffffu, lg, 8));
                mx = fmaxf(mx, __shfl_xor_sync(0xffffffffu, mx, 16));
                const float mn = fmaxf(m, mx);
                const float alpha = exp_diff(m, mn);
                const float p = exp_diff(lg, mn);
                m = mn;
                const int myrow = row0 + (lane >> 3);
                const float vsc = __uint_as_float(lds16(slot + OFF_VS + myrow * 4 + (lane & 1) * 2) << 16);
                const float vzc = __uint_as_float(lds16(slot + OFF_VZ + myrow * 4 + (lane & 1) * 2) << 16);
                const float c = p * vsc;
                lsum = fmaf(lsum, alpha, p);
                zsum = fmaf(zsum, alpha, c * vzc);
                acc0 *= alpha; acc1 *= alpha; acc2 *= alpha; acc3 *= alpha;
#pragma unroll
                for (int r = 0; r < 4; r++) {
                    const int4 v = lds128(slot + OFF_V + (row0 + r) * 512 + lane * 16);
                    const float cr = __shfl_sync(0xffffffffu, c, 8 * r + hw);
                    acc0 = fmaf(cr, (float)v.x, acc0);
                    acc1 = fmaf(cr, (float)v.y, acc1);
                    acc2 = fmaf(cr, (float)v.z, acc2);
                    acc3 = fmaf(cr, (float)v.w, acc3);
                }
            }
            __syncwarp();
            if (lane == 0) mbar_arrive(smem_u32(&s_empty[s]));
            if (++s == NST) { s = 0; ph ^= 1; }
        }
        __threadfence();
    }
    __syncthreads();

    if (threadIdx.x == 0) {
        atomicAdd(&g_done, 1);
        int it = 0;
        while (*(volatile unsigned int*)&g_done < (unsigned)nct) { if (++it > (1 << 24)) __trap(); }
        __threadfence();
    }
    __syncthreads();
    float* red = reinterpret_cast<float*>(smem);
    for (int o = blockIdx.x; o < H * 4; o += nct) {
        const int h = o >> 2, col = (o & 3) * 32 + lane;
        const float* base = g_part + (size_t)h * MAXCTA * PART_STRIDE;
        float M = NEG_INF;
        for (int c = lane; c < nct; c += 32) M = fmaxf(M, __ldcg(base + c * PART_STRIDE + D));
#pragma unroll
        for (int x = 16; x > 0; x >>= 1) M = fmaxf(M, __shfl_xor_sync(0xffffffffu, M, x));
        float a = 0.f, L = 0.f;
        for (int c = warp; c < nct; c += NCW + 1) {
            const float2 ml = __ldcg(reinterpret_cast<const float2*>(base + c * PART_STRIDE + D));
            const float e = exp_diff(ml.x, M);
            a = fmaf(e, __ldcg(base + c * PART_STRIDE + col), a);
            L = fmaf(e, ml.y, L);
        }
        red[warp * 64 + lane] = a;
        red[warp * 64 + 32 + lane] = L;
        __syncthreads();
        if (warp == 0) {
            float A = 0.f, LL = 0.f;
#pragma unroll
            for (int w = 0; w < NCW + 1; w++) { A += red[w * 64 + lane]; LL += red[w * 64 + 32 + lane]; }
            out[h * D + col] = __float2bfloat16_rn(A / LL);
        }
        __syncthreads();
    }
    if (threadIdx.x == 0) {
        if (atomicAdd(&g_exit, 1) == (unsigned)nct - 1) { g_ticket = 0; g_done = 0; g_exit = 0; }
    }
}

}

extern "C" void kernel_launch(void* const* d_in, const int* in_sizes, int n_in, void* d_out, int out_size) {
    static int nsm = 0;
    if (nsm == 0) {
        int dev = 0;
        cudaGetDevice(&dev);
        cudaDeviceGetAttribute(&nsm, cudaDevAttrMultiProcessorCount, dev);
        if (nsm > MAXCTA) nsm = MAXCTA;
        cudaFuncSetAttribute(kv_decode_kernel, cudaFuncAttributeMaxDynamicSharedMemorySize, SMEM_BYTES);
    }
    kv_decode_kernel<<<nsm, NTHREADS, SMEM_BYTES>>>(
        (const __nv_bfloat16*)d_in[0], (const int*)d_in[1], (const __nv_bfloat16*)d_in[2],
        (const __nv_bfloat16*)d_in[3], (const int*)d_in[4], (const __nv_bfloat16*)d_in[5],
        (const __nv_bfloat16*)d_in[6], (const __nv_bfloat16*)d_in[7], (const __nv_bfloat16*)d_in[8],
        (const __nv_bfloat16*)d_in[9], (const __nv_bfloat16*)d_in[10], (__nv_bfloat16*)d_out);
}
```

```cpp
#include <cuda_runtime.h>
#include <cuda.h>
#include <cuda_bf16.h>
#include <stdint.h>

#define KP 16
#define KNST 8
#define KQW 32
#define KNT 10
#define KTB 8192
#define KLIM 16
#define KLIMT 10
#define X_FREE 0
#define X_B0 0
#define X_B1 0
#define X_W0 8448
#define X_BACKOFF 100
#define X_SLEEP 64
#define X_LAG 1
#define X_PROMO CU_TENSOR_MAP_L2_PROMOTION_NONE
#define NCW 8
#define NHW 4
#define NTHREADS ((1 + NHW + NCW) * 32)

namespace {

constexpr int H = 32, S = 8192, D = 128;
constexpr int P = KP, NST = KNST;
constexpr int BPH = S / P;
constexpr int NITEMS = BPH * H;
constexpr int RPW = P / NCW;
constexpr int MAXCTA = 144;
static_assert(RPW == 2 || RPW == 4, "rows per warp");

constexpr int QW = KQW, OPH = D / QW, NOWN = H * OPH;
constexpr int LR = QW / 4, RPI = 32 / LR;
constexpr uint32_t T_BYTES = KTB;
constexpr int NT = KNT, TROWS = T_BYTES / (QW * 4), R = NT * TROWS;
constexpr int KPL = T_BYTES / (NCW * 512);
constexpr uint32_t HK = R / P;
constexpr int HROWS = TROWS / NHW;
constexpr int NW = (NT * HROWS + 31) / 32;
constexpr int NJ = (MAXCTA + NHW * RPI - 1) / (NHW * RPI);
static_assert(R % P == 0 && R < S && NST <= 8 && KPL >= 1, "held-back rows");

constexpr uint32_t KV_BYTES = P * D * 4;
constexpr uint32_t CS_BYTES = P * D * 2;
constexpr uint32_t SC_BYTES = P * 4;
constexpr uint32_t OFF_K = 0, OFF_V = KV_BYTES, OFF_C = 2 * KV_BYTES, OFF_S = OFF_C + CS_BYTES;
constexpr uint32_t OFF_KS = OFF_S + CS_BYTES, OFF_KZ = OFF_KS + SC_BYTES, OFF_VS = OFF_KZ + SC_BYTES,
                   OFF_VZ = OFF_VS + SC_BYTES;
constexpr uint32_t SLOT_TX = OFF_VZ + SC_BYTES;
constexpr uint32_t SLOT = (SLOT_TX + 127) / 128 * 128;
constexpr uint32_t OFF_Q = NST * SLOT;
constexpr uint32_t OFF_QC = OFF_Q + H * D * 2, OFF_QS = OFF_QC + D * 2;
constexpr uint32_t Q_TX = H * D * 2 + 2 * D * 2;
constexpr uint32_t OFF_RED = OFF_Q + Q_TX;
constexpr uint32_t RED_STRIDE = D + 4;
constexpr uint32_t OFF_W = OFF_RED + 2 * NCW * RED_STRIDE * 4;
constexpr uint32_t OFF_TR = OFF_W + R * 4;
constexpr uint32_t OFF_HB = OFF_TR + NCW * QW * 4;
constexpr uint32_t SMEM_BYTES = OFF_HB + 2 * NHW * QW * 4;

__device__ float4 g_acc[H * MAXCTA * 32];
__device__ float2 g_ml[H * MAXCTA];
__device__ uint2 g_row[H * 2 * R];
__device__ unsigned int g_ticket;
__device__ unsigned int g_epoch;
#define STAMP(i)

__device__ __forceinline__ uint32_t smem_u32(const void* p) { return (uint32_t)__cvta_generic_to_shared(p); }
__device__ __forceinline__ bool elect_one() {
    uint32_t p;
    asm volatile("{ .reg .pred p; elect.sync _|p, 0xffffffff; selp.u32 %0, 1, 0, p; }" : "=r"(p));
    return p;
}
__device__ __forceinline__ uint32_t opaque_zero() {
    uint32_t z;
    asm volatile("mov.u32 %0, 0;" : "=r"(z));
    return z;
}
__device__ __forceinline__ void mbar_init(uint32_t bar, uint32_t cnt) {
    asm volatile("mbarrier.init.shared.b64 [%0], %1;" ::"r"(bar), "r"(cnt) : "memory");
}
__device__ __forceinline__ void mbar_expect_tx(uint32_t bar, uint32_t bytes) {
    asm volatile("mbarrier.arrive.expect_tx.shared.b64 _, [%0], %1;" ::"r"(bar), "r"(bytes) : "memory");
}
__device__ __forceinline__ void mbar_arrive(uint32_t bar) {
    asm volatile("mbarrier.arrive.shared.b64 _, [%0];" ::"r"(bar) : "memory");
}
__device__ __forceinline__ void mbar_wait(uint32_t bar, uint32_t parity) {
    uint32_t done;
    int it = 0;
    do {
        asm volatile("{ .reg .pred p; mbarrier.try_wait.parity.shared.b64 p, [%1], %2; selp.u32 %0, 1, 0, p; }"
                     : "=r"(done) : "r"(bar), "r"(parity) : "memory");
        if (++it > (1 << 24)) __trap();
    } while (!done);
}
__device__ __forceinline__ void bulk_g2s(uint32_t dst, const void* src, uint32_t bytes, uint32_t bar) {
    asm volatile("cp.async.bulk.shared::cluster.global.mbarrier::complete_tx::bytes [%0], [%1], %2, [%3];"
                 ::"r"(dst), "l"(src), "r"(bytes), "r"(bar) : "memory");
}
__device__ __forceinline__ void bulk_g2s_hint(uint32_t dst, const void* src, uint32_t bytes, uint32_t bar, uint64_t pol) {
    asm volatile("cp.async.bulk.shared::cluster.global.mbarrier::complete_tx::bytes.L2::cache_hint [%0], [%1], %2, [%3], %4;"
                 ::"r"(dst), "l"(src), "r"(bytes), "r"(bar), "l"(pol) : "memory");
}
__device__ __forceinline__ int4 lds128(uint32_t a) {
    int4 v;
    asm volatile("ld.shared.v4.s32 {%0,%1,%2,%3}, [%4];" : "=r"(v.x), "=r"(v.y), "=r"(v.z), "=r"(v.w) : "r"(a));
    return v;
}
__device__ __forceinline__ uint2 lds64(uint32_t a) {
    uint2 v;
    asm volatile("ld.shared.v2.u32 {%0,%1}, [%2];" : "=r"(v.x), "=r"(v.y) : "r"(a));
    return v;
}
__device__ __forceinline__ uint32_t lds32(uint32_t a) {
    uint32_t v;
    asm volatile("ld.shared.u32 %0, [%1];" : "=r"(v) : "r"(a));
    return v;
}
__device__ __forceinline__ uint32_t lds16(uint32_t a) {
    uint16_t v;
    asm volatile("ld.shared.u16 %0, [%1];" : "=h"(v) : "r"(a));
    return v;
}
__device__ __forceinline__ uint32_t bf2_mul(uint32_t a, uint32_t b) {
    uint32_t d; asm("mul.rn.bf16x2 %0, %1, %2;" : "=r"(d) : "r"(a), "r"(b)); return d;
}
__device__ __forceinline__ uint32_t bf2_add(uint32_t a, uint32_t b) {
    uint32_t d; asm("add.rn.bf16x2 %0, %1, %2;" : "=r"(d) : "r"(a), "r"(b)); return d;
}
__device__ __forceinline__ uint32_t bf2_sub(uint32_t a, uint32_t b) {
    uint32_t d; asm("sub.rn.bf16x2 %0, %1, %2;" : "=r"(d) : "r"(a), "r"(b)); return d;
}
__device__ __forceinline__ uint32_t bf2_pack(float lo, float hi) {
    uint32_t d; asm("cvt.rn.bf16x2.f32 %0, %1, %2;" : "=r"(d) : "f"(hi), "f"(lo)); return d;
}
__device__ __forceinline__ float bf_lo(uint32_t v) { return __uint_as_float(v << 16); }
__device__ __forceinline__ float bf_hi(uint32_t v) { return __uint_as_float(v & 0xffff0000u); }
__device__ __forceinline__ float bf_round(float x) { return __bfloat162float(__float2bfloat16_rn(x)); }
__device__ __forceinline__ float ex2(float x) { float y; asm("ex2.approx.ftz.f32 %0, %1;" : "=f"(y) : "f"(x)); return y; }

constexpr float LOG2E = 1.4426950408889634f;
constexpr float NEG_INF = -__builtin_huge_valf();

__device__ __forceinline__ float exp_diff(float a, float b) {
    return (a == NEG_INF) ? 0.f : ex2((a - b) * LOG2E);
}

__device__ __forceinline__ uint32_t tagw(float x, uint32_t tag) { return (__float_as_uint(x) & ~1u) | tag; }
__device__ __forceinline__ float untag(uint32_t x) { return __uint_as_float(x & ~1u); }
__device__ __forceinline__ void publish(int h, int lane, float4 a, float M, float L, uint32_t tag) {
    float4* pa = g_acc + (size_t)(h * MAXCTA + blockIdx.x) * 32 + lane;
    asm volatile("st.relaxed.gpu.global.v4.b32 [%0], {%1,%2,%3,%4};" ::"l"(pa), "r"(tagw(a.x, tag)), "r"(tagw(a.y, tag)),
                 "r"(tagw(a.z, tag)), "r"(tagw(a.w, tag)) : "memory");
    if (lane == 0)
        asm volatile("st.relaxed.gpu.global.v2.b32 [%0], {%1,%2};" ::"l"(g_ml + h * MAXCTA + blockIdx.x),
                     "r"(tagw(M, tag)), "r"(tagw(L, tag)) : "memory");
}

__device__ __forceinline__ void reduce_groups(float* dst, float o0, float o1, float o2, float o3, int lane) {
    const bool hi = lane & 16;
    const float r0 = (hi ? o2 : o0) + __shfl_xor_sync(0xffffffffu, hi ? o0 : o2, 16);
    const float r1 = (hi ? o3 : o1) + __shfl_xor_sync(0xffffffffu, hi ? o1 : o3, 16);
    dst += (lane & (LR - 1)) * 4 + hi * 2;
    if (RPI == 4) {
        const bool up = lane & 8;
        dst[up] = (up ? r1 : r0) + __shfl_xor_sync(0xffffffffu, up ? r0 : r1, 8);
    } else {
        *reinterpret_cast<float2*>(dst) = make_float2(r0, r1);
    }
}

__device__ __forceinline__ uint32_t held0(uint32_t h) { return X_B0 + h * X_B1; }
constexpr uint32_t W0 = X_W0, LAST0 = (H - 1) * BPH + X_B0 + (H - 1) * X_B1;
__device__ __forceinline__ uint32_t item_index(uint32_t i) {
    return i - W0 < HK ? LAST0 + i - W0 : i - W0 < LAST0 + HK - W0 ? i - HK : i;
}
__device__ __forceinline__ uint32_t stream_head(uint32_t i) {
    return i - W0 < HK ? W0 / BPH : min(item_index(i) / BPH, (uint32_t)H);
}

__global__ void __launch_bounds__(NTHREADS, 1)
kv_decode_kernel(const __grid_constant__ CUtensorMap vmap, const __nv_bfloat16* __restrict__ q, const int* __restrict__ qk,
                 const __nv_bfloat16* __restrict__ ks, const __nv_bfloat16* __restrict__ kz,
                 const int* __restrict__ qv, const __nv_bfloat16* __restrict__ vs,
                 const __nv_bfloat16* __restrict__ vz, const __nv_bfloat16* __restrict__ q_cos,
                 const __nv_bfloat16* __restrict__ q_sin, const __nv_bfloat16* __restrict__ k_cos,
                 const __nv_bfloat16* __restrict__ k_sin, __nv_bfloat16* __restrict__ out) {
    extern __shared__ __align__(128) unsigned char smem[];
    __shared__ __align__(8) uint64_t s_full[NST], s_empty[NST], s_qbar, s_wbar;
    __shared__ volatile int s_meta[NST];
    __shared__ volatile int s_flushed;
    __shared__ float4 s_hm[2][NHW];
    __shared__ uint32_t s_epoch;
    const int warp = threadIdx.x >> 5, lane = threadIdx.x & 31;
    const uint32_t sbase = smem_u32(smem);
    const uint32_t nct = gridDim.x;

    if (warp == 0) {
        const bool leader = elect_one();
        if (leader) {
            STAMP(0);
#pragma unroll
            for (int s = 0; s < NST; s++) { mbar_init(smem_u32(&s_full[s]), 1); mbar_init(smem_u32(&s_empty[s]), NCW); }
            mbar_init(smem_u32(&s_qbar), 1);
            mbar_init(smem_u32(&s_wbar), NHW);
            asm volatile("fence.mbarrier_init.release.cluster;" ::: "memory");
        }
        __syncwarp();
        asm volatile("bar.arrive 2, %0;" ::"n"(NTHREADS) : "memory");
        if (leader) {
            uint64_t pol;
            asm volatile("createpolicy.fractional.L2::evict_first.b64 %0, 1.0;" : "=l"(pol));
            mbar_expect_tx(smem_u32(&s_qbar), Q_TX);
            bulk_g2s(sbase + OFF_Q, q, H * D * 2, smem_u32(&s_qbar));
            bulk_g2s(sbase + OFF_QC, q_cos, D * 2, smem_u32(&s_qbar));
            bulk_g2s(sbase + OFF_QS, q_sin, D * 2, smem_u32(&s_qbar));
            int s = 0, ph = 1, cnt = 0;
            int ls = 0, lph = 0, fl = 0, ret = NST;
            uint32_t cost = 0;
            constexpr int KU = KV_BYTES / 4096, NPRE = KLIM / (2 * KU);
            const uint32_t tbase = (NPRE + 1) * nct, twrap = NITEMS - tbase + nct - 1;
            uint32_t cur = blockIdx.x, nxt = cur + nct, pend = nxt + nct - tbase;
#pragma unroll 1
            for (uint32_t live = opaque_zero();; live++) {
                do {
                    const uint32_t idx = item_index(cur), blk = idx & (BPH - 1);
                    const uint32_t hb = blk - held0(idx / BPH);
                    const bool held = hb < HK;
                    fl += held ? KU : 2 * KU;
                    while (fl > KLIM || (KLIM > NST * KU && cnt == ret)) {
                        mbar_wait(smem_u32(&s_full[ls]), lph);
                        fl -= (cost >> 4 * ls) & 15;
                        ret++;
                        if (++ls == NST) { ls = 0; lph ^= 1; }
                    }
                    if (cnt >= NST) mbar_wait(smem_u32(&s_empty[s]), ph);
                    cost = (cost & ~(15u << 4 * s)) | (held ? KU : 2 * KU) << 4 * s;
                    const uint32_t bar = smem_u32(&s_full[s]), dst = sbase + s * SLOT;
                    s_meta[s] = stream_head(nxt) | idx / BPH << 8 | (held ? (hb + 1) << 16 : 0);
                    mbar_expect_tx(bar, held ? SLOT_TX - KV_BYTES : SLOT_TX);
                    bulk_g2s_hint(dst + OFF_K, qk + (size_t)idx * (P * D), KV_BYTES, bar, pol);
                    bulk_g2s(dst + OFF_C, k_cos + blk * (P * D), CS_BYTES, bar);
                    bulk_g2s(dst + OFF_S, k_sin + blk * (P * D), CS_BYTES, bar);
                    bulk_g2s_hint(dst + OFF_KS, ks + idx * (P * 2), SC_BYTES, bar, pol);
                    bulk_g2s_hint(dst + OFF_KZ, kz + idx * (P * 2), SC_BYTES, bar, pol);
                    if (!held) bulk_g2s_hint(dst + OFF_V, qv + (size_t)idx * (P * D), KV_BYTES, bar, pol);
                    bulk_g2s_hint(dst + OFF_VS, vs + idx * (P * 2), SC_BYTES, bar, pol);
                    bulk_g2s_hint(dst + OFF_VZ, vz + idx * (P * 2), SC_BYTES, bar, pol);
                    cnt++;
                    if (++s == NST) { s = 0; ph ^= 1; }
                    cur = nxt;
                    if (cur >= (uint32_t)NITEMS) break;
                    nxt = pend + tbase;
                    if (cnt < NPRE - 1) pend += nct;
                    else if (nxt < (uint32_t)NITEMS)
                        asm volatile("atom.relaxed.gpu.global.inc.u32 %0, [%1], %2;" : "=r"(pend) : "l"(&g_ticket), "r"(twrap) : "memory");
                } while (live || cnt < NPRE);
                asm volatile("prefetch.tensormap [%0];" ::"l"(&vmap) : "memory");
#pragma unroll 1
                for (int o = blockIdx.x; o < NOWN; o += nct) {
#pragma unroll 1
                    for (int t = live ? 0 : NT - 1; t < NT; t++) {
                        if (live) {
                            fl += T_BYTES / 4096;
                            while ((fl > KLIMT && t < NT - X_FREE) || cnt == ret) {
                                mbar_wait(smem_u32(&s_full[ls]), lph);
                                fl -= (cost >> 4 * ls) & 15;
                        ret++;
                                if (++ls == NST) { ls = 0; lph ^= 1; }
                            }
                            mbar_wait(smem_u32(&s_empty[s]), ph);
                            cost = (cost & ~(15u << 4 * s)) | (T_BYTES / 4096) << 4 * s;
                            cnt++;
                        }
                        asm volatile("{ .reg .pred p; setp.ne.u32 p, %6, 0;\n"
                                     "@p mbarrier.arrive.expect_tx.shared.b64 _, [%2], %7;\n"
                                     "@p cp.async.bulk.tensor.2d.shared::cluster.global.mbarrier::complete_tx::bytes.L2::cache_hint "
                                     "[%0], [%1, {%3, %4}], [%2], %5; }" ::"r"(sbase + s * SLOT), "l"(&vmap), "r"(smem_u32(&s_full[s])),
                                     "r"((o % OPH) * QW), "r"((o / OPH) * S + held0(o / OPH) * P + t * TROWS), "l"(pol), "r"(live), "n"(T_BYTES) : "memory");
                        if (live && ++s == NST) { s = 0; ph ^= 1; }
                    }
                }
                if (live) break;
            }
        }
    } else if (warp <= NHW) {
        const int mw = warp - 1;
        if (threadIdx.x == 32) { s_epoch = *(volatile unsigned int*)&g_epoch; s_flushed = 0; }
        asm volatile("bar.sync 2, %0;" ::"n"(NTHREADS) : "memory");
        const uint32_t tag = (s_epoch + 1) & 1;
        float* sw = reinterpret_cast<float*>(smem + OFF_W);
        const float* tr = reinterpret_cast<const float*>(smem + OFF_TR);
#pragma unroll 1
        for (int o = blockIdx.x; o < NOWN; o += nct) {
            const int h = o / OPH, col0 = (o % OPH) * QW;
            const uint2* pr = g_row + (h * 2 + col0 / 64) * R + mw * HROWS;
            const int c0 = mw * RPI + lane / LR;
            const float4* pa = g_acc + (size_t)(h * MAXCTA + c0) * 32 + col0 / 4 + (lane & (LR - 1));
            const float2* pm = g_ml + h * MAXCTA + c0;
#pragma unroll 1
            for (uint32_t live = opaque_zero();; live++) {
                uint2 rw[NW];
                uint32_t bad = 0;
#pragma unroll
                for (int j = 0; j < NW; j++) {
                    rw[j] = make_uint2(0xff800000u, 0);
                    if (live && lane + 32 * j < NT * HROWS) bad |= 1u << j;
                }
                for (int k = 0; live && s_flushed <= (h == H - 1 ? min((int)(W0 / BPH) + 1, H - 2) : h); k++) { __nanosleep(X_SLEEP); if (k > (1 << 24)) __trap(); }
                for (int it = 0;; it++) {
#pragma unroll
                    for (int j = 0; j < NW; j++) {
                        const int i = lane + 32 * j;
                        asm volatile("{ .reg .pred p; .reg .b64 t; setp.ne.u32 p, %2, 0; mov.b64 t, {%0, %1};\n"
                                     "@p ld.relaxed.gpu.global.b64 t, [%3]; mov.b64 {%0, %1}, t; }"
                                     : "+r"(rw[j].x), "+r"(rw[j].y)
                                     : "r"(bad & (1u << j)), "l"(pr + i / HROWS * TROWS + i % HROWS) : "memory");
                    }
                    uint32_t nb = 0;
#pragma unroll
                    for (int j = NW - 1; j >= 0; j--) nb = nb * 2 + ((rw[j].x ^ tag) & 1);
                    bad &= nb;
                    if (!__any_sync(0xffffffffu, bad)) break;
                    __nanosleep(400);
                    if (it > (1 << 22)) __trap();
                }
                float Mr = NEG_INF, Lr = 0.f, Zr = 0.f;
#pragma unroll
                for (int j = 0; j < NW; j++) Mr = fmaxf(Mr, untag(rw[j].x));
#pragma unroll
                for (int x = 16; x > 0; x >>= 1) Mr = fmaxf(Mr, __shfl_xor_sync(0xffffffffu, Mr, x));
#pragma unroll
                for (int j = 0; j < NW; j++) {
                    const int i = lane + 32 * j;
                    const float p = exp_diff(untag(rw[j].x), Mr), w = p * bf_hi(rw[j].y);
                    Lr += p;
                    Zr = fmaf(w, bf_lo(rw[j].y), Zr);
                    if (i < NT * HROWS) sw[i / HROWS * TROWS + mw * HROWS + i % HROWS] = w;
                }
                __syncwarp();
                if (lane == 0 && live) mbar_arrive(smem_u32(&s_wbar));
#pragma unroll
                for (int x = 16; x > 0; x >>= 1) { Lr += __shfl_xor_sync(0xffffffffu, Lr, x); Zr += __shfl_xor_sync(0xffffffffu, Zr, x); }
                if (threadIdx.x == 32) STAMP(8);
                uint4 a[NJ]; uint2 ml[NJ];
#pragma unroll
                for (int j = 0; j < NJ; j++) {
                    a[j] = make_uint4(0, 0, 0, 0); ml[j] = make_uint2(0xff800000u, 0);
                    if (live && c0 + NHW * RPI * j < nct) bad |= 1u << j;
                }
                for (int k = 0; live && s_flushed <= min(h + X_LAG, H - 1); k++) { __nanosleep(X_SLEEP); if (k > (1 << 24)) __trap(); }
                if (threadIdx.x == 32) STAMP(9);
                for (int it = 0;; it++) {
#pragma unroll
                    for (int j = 0; j < NJ; j++) {
                        asm volatile("{ .reg .pred p; setp.ne.u32 p, %6, 0;\n"
                                     "@p ld.relaxed.gpu.global.v4.b32 {%0,%1,%2,%3}, [%7];\n"
                                     "@p ld.relaxed.gpu.global.v2.b32 {%4,%5}, [%8]; }"
                                     : "+r"(a[j].x), "+r"(a[j].y), "+r"(a[j].z), "+r"(a[j].w), "+r"(ml[j].x), "+r"(ml[j].y)
                                     : "r"(bad & (1u << j)), "l"(pa + NHW * RPI * 32 * j), "l"(pm + NHW * RPI * j) : "memory");
                    }
                    uint32_t nb = 0;
#pragma unroll
                    for (int j = NJ - 1; j >= 0; j--) {
                        uint32_t x;
                        asm volatile("{ .reg .b32 u, v;\n"
                            "lop3.b32 u, %1, %2, %7, 0x7e;\n lop3.b32 v, %3, %4, %7, 0x7e;\n lop3.b32 %0, %5, %6, %7, 0x7e;\n"
                            "lop3.b32 %0, %0, u, v, 0xfe; }"
                            : "=r"(x) : "r"(a[j].x), "r"(a[j].y), "r"(a[j].z), "r"(a[j].w), "r"(ml[j].x), "r"(ml[j].y), "r"(tag));
                        nb = nb * 2 + (x & 1);
                    }
                    bad &= nb;
                    if (threadIdx.x == 32 && it == 0) STAMP(14);
                    if (!__any_sync(0xffffffffu, bad)) break;
                    if (X_BACKOFF) __nanosleep(X_BACKOFF);
                    if (it > (1 << 22)) __trap();
                }
                if (lane == 0) STAMP(10 + mw);
                float M = Mr;
#pragma unroll
                for (int j = 0; j < NJ; j++) M = fmaxf(M, untag(ml[j].x));
#pragma unroll
                for (int x = 16; x >= LR; x >>= 1) M = fmaxf(M, __shfl_xor_sync(0xffffffffu, M, x));
                const float fr = exp_diff(Mr, M);
                float o0 = 0.f, o1 = 0.f, o2 = 0.f, o3 = 0.f, L = 0.f;
#pragma unroll
                for (int j = 0; j < NJ; j++) {
                    const float e = exp_diff(untag(ml[j].x), M);
                    o0 = fmaf(e, untag(a[j].x), o0); o1 = fmaf(e, untag(a[j].y), o1);
                    o2 = fmaf(e, untag(a[j].z), o2); o3 = fmaf(e, untag(a[j].w), o3);
                    L = fmaf(e, untag(ml[j].y), L);
                }
                float* hb = reinterpret_cast<float*>(smem + OFF_HB) + live * NHW * QW;
                reduce_groups(hb + mw * QW, o0, o1, o2, o3, lane);
#pragma unroll
                for (int x = 16; x >= LR; x >>= 1) L += __shfl_xor_sync(0xffffffffu, L, x);
                if (lane == 0) s_hm[live][mw] = make_float4(M, fmaf(fr, Lr, L), fr, fr * Zr);
                asm volatile("bar.sync 3, %0;" ::"n"(NHW * 32) : "memory");
                float MM = NEG_INF, LL = 0.f, base = 0.f, g[NHW];
                const int col = (mw * 32 + lane) & (QW - 1);
#pragma unroll
                for (int w = 0; w < NHW; w++) MM = fmaxf(MM, s_hm[live][w].x);
#pragma unroll
                for (int w = 0; w < NHW; w++) {
                    const float4 x = s_hm[live][w];
                    const float e = exp_diff(x.x, MM);
                    LL = fmaf(e, x.y, LL);
                    base = fmaf(e, hb[w * QW + col] - x.w, base);
                    g[w] = e * x.z;
                }
                const float inv = __frcp_rn(LL);
                base *= inv;
#pragma unroll
                for (int w = 0; w < NHW; w++) g[w] *= inv;
                if (threadIdx.x == 32 && live) STAMP(5);
                asm volatile("{ .reg .pred p; setp.ne.u32 p, %0, 0; @p bar.sync 4, %1; }" ::"r"(live), "n"((NHW + NCW) * 32) : "memory");
#pragma unroll
                for (int w = 0; w < NHW; w++) {
                    float y = tr[w * (NCW / NHW) * QW + col];
#pragma unroll
                    for (int k = 1; k < NCW / NHW; k++) y += tr[(w * (NCW / NHW) + k) * QW + col];
                    g[w] *= y;
                }
                float y = base;
#pragma unroll
                for (int w = 0; w < NHW; w += 2) y += g[w] + g[w + 1];
                if (live && mw < QW / 32) out[h * D + col0 + col] = __float2bfloat16_rn(y);
                if (live) break;
            }
            if (o == NOWN - 1 && threadIdx.x == 32) g_epoch = s_epoch + 1;
        }
        if (threadIdx.x == 32) STAMP(6);
    } else {
        const int cw = warp - 1 - NHW;
        const int hw = lane >> 4, li = lane & 15;
        int s = 0, ph = 0;
#pragma unroll 1
        for (uint32_t live = opaque_zero();; live++) {
        if (live) {
        asm volatile("bar.sync 2, %0;" ::"n"(NTHREADS) : "memory");
        const uint32_t tag = (s_epoch + 1) & 1;
        mbar_wait(smem_u32(&s_qbar), 0);
        if (threadIdx.x == NTHREADS - 32) STAMP(1);
        int cur = stream_head(blockIdx.x), nflush = 0, qh = -1;
        if (cw == 0) for (int e = 0; e < cur; e++) publish(e, lane, make_float4(0, 0, 0, 0), NEG_INF, 0.f, tag);
        float4 qlo, qhi;
        while (true) {
            float m = NEG_INF, lsum = 0.f, zsum = 0.f;
            float acc0 = 0.f, acc1 = 0.f, acc2 = 0.f, acc3 = 0.f;
            int nh;
            do {
                mbar_wait(smem_u32(&s_full[s]), ph);
                const int meta = s_meta[s];
                nh = meta & 255;
                if (((meta >> 8) & 255) != qh) {
                    qh = (meta >> 8) & 255;
                    const uint2 l = lds64(sbase + OFF_Q + qh * 256 + li * 8), h = lds64(sbase + OFF_Q + qh * 256 + 128 + li * 8);
                    const uint2 cl = lds64(sbase + OFF_QC + li * 8), ch = lds64(sbase + OFF_QC + 128 + li * 8);
                    const uint2 sl = lds64(sbase + OFF_QS + li * 8), sh = lds64(sbase + OFF_QS + 128 + li * 8);
                    const uint32_t rl0 = bf2_sub(bf2_mul(l.x, cl.x), bf2_mul(h.x, sl.x));
                    const uint32_t rl1 = bf2_sub(bf2_mul(l.y, cl.y), bf2_mul(h.y, sl.y));
                    const uint32_t rh0 = bf2_add(bf2_mul(h.x, ch.x), bf2_mul(l.x, sh.x));
                    const uint32_t rh1 = bf2_add(bf2_mul(h.y, ch.y), bf2_mul(l.y, sh.y));
                    qlo = make_float4(bf_lo(rl0), bf_hi(rl0), bf_lo(rl1), bf_hi(rl1));
                    qhi = make_float4(bf_lo(rh0), bf_hi(rh0), bf_lo(rh1), bf_hi(rh1));
                }
                const uint32_t slot = sbase + s * SLOT;
                const int row0 = cw * RPW;
                float dot[RPW / 2];
#pragma unroll
                for (int it = 0; it < RPW / 2; it++) {
                    const int row = row0 + (RPW / 2) * hw + it;
                    const int4 a = lds128(slot + OFF_K + row * 512 + li * 16);
                    const int4 b = lds128(slot + OFF_K + row * 512 + 256 + li * 16);
                    const uint2 cl = lds64(slot + OFF_C + row * 256 + li * 8);
                    const uint2 ch = lds64(slot + OFF_C + row * 256 + 128 + li * 8);
                    const uint2 sl = lds64(slot + OFF_S + row * 256 + li * 8);
                    const uint2 sh = lds64(slot + OFF_S + row * 256 + 128 + li * 8);
                    const uint32_t sc = lds32(slot + OFF_KS + row * 4);
                    const uint32_t zc = lds32(slot + OFF_KZ + row * 4);
                    const uint32_t s0 = __byte_perm(sc, 0, 0x1010), s1 = __byte_perm(sc, 0, 0x3232);
                    const uint32_t z0 = __byte_perm(zc, 0, 0x1010), z1 = __byte_perm(zc, 0, 0x3232);
                    const uint32_t l0 = bf2_mul(bf2_sub(bf2_pack((float)a.x, (float)a.y), z0), s0);
                    const uint32_t l1 = bf2_mul(bf2_sub(bf2_pack((float)a.z, (float)a.w), z0), s0);
                    const uint32_t h0 = bf2_mul(bf2_sub(bf2_pack((float)b.x, (float)b.y), z1), s1);
                    const uint32_t h1 = bf2_mul(bf2_sub(bf2_pack((float)b.z, (float)b.w), z1), s1);
                    const uint32_t rl0 = bf2_sub(bf2_mul(l0, cl.x), bf2_mul(h0, sl.x));
                    const uint32_t rl1 = bf2_sub(bf2_mul(l1, cl.y), bf2_mul(h1, sl.y));
                    const uint32_t rh0 = bf2_add(bf2_mul(h0, ch.x), bf2_mul(l0, sh.x));
                    const uint32_t rh1 = bf2_add(bf2_mul(h1, ch.y), bf2_mul(l1, sh.y));
                    float d0 = qlo.x * bf_lo(rl0), d1 = qhi.x * bf_lo(rh0);
                    float d2 = qlo.z * bf_lo(rl1), d3 = qhi.z * bf_lo(rh1);
                    d0 = fmaf(qlo.y, bf_hi(rl0), d0); d1 = fmaf(qhi.y, bf_hi(rh0), d1);
                    d2 = fmaf(qlo.w, bf_hi(rl1), d2); d3 = fmaf(qhi.w, bf_hi(rh1), d3);
                    dot[it] = (d0 + d1) + (d2 + d3);
                }
                int4 v[RPW];
#pragma unroll
                for (int r = 0; r < RPW; r++) v[r] = lds128(slot + OFF_V + (row0 + r) * 512 + lane * 16);
                constexpr int LPR = 32 / RPW;
                const int myrow = row0 + lane / LPR;
                const uint32_t vsb = lds16(slot + OFF_VS + myrow * 4 + (lane & 1) * 2);
                const uint32_t vzb = lds16(slot + OFF_VZ + myrow * 4 + (lane & 1) * 2);
                const float vsc = __uint_as_float(vsb << 16), vzc = __uint_as_float(vzb << 16);
                __syncwarp();
                if (lane == 0) mbar_arrive(smem_u32(&s_empty[s]));
                if (++s == NST) { s = 0; ph ^= 1; }
                float t;
                if (RPW == 4) {
                    const bool up = lane & 8;
                    t = (up ? dot[RPW / 2 - 1] : dot[0]) + __shfl_xor_sync(0xffffffffu, up ? dot[0] : dot[RPW / 2 - 1], 8);
                } else {
                    t = dot[0] + __shfl_xor_sync(0xffffffffu, dot[0], 8);
                }
                t += __shfl_xor_sync(0xffffffffu, t, 4);
                t += __shfl_xor_sync(0xffffffffu, t, 2);
                t += __shfl_xor_sync(0xffffffffu, t, 1);
                const float lg = bf_round(bf_round(t) * 0.08838834764831845f);
                if (meta >> 16) {
                    if ((lane & (LPR - 1)) < 2)
                        asm volatile("{ .reg .b64 t; mov.b64 t, {%1, %2}; st.relaxed.gpu.global.b64 [%0], t; }"
                                     ::"l"(g_row + (qh * 2 + (lane & 1)) * R + ((meta >> 16) - 1) * P + myrow),
                                     "r"(__float_as_uint(lg) | tag), "r"(vsb << 16 | vzb) : "memory");
                    continue;
                }
                float mx = fmaxf(lg, __shfl_xor_sync(0xffffffffu, lg, 16));
                if (RPW == 4) mx = fmaxf(mx, __shfl_xor_sync(0xffffffffu, mx, 8));
                const float mn = fmaxf(m, mx);
                const float alpha = exp_diff(m, mn);
                const float p = exp_diff(lg, mn);
                m = mn;
                const float c = p * vsc;
                lsum = fmaf(lsum, alpha, p);
                zsum = fmaf(zsum, alpha, c * vzc);
                acc0 *= alpha; acc1 *= alpha; acc2 *= alpha; acc3 *= alpha;
#pragma unroll
                for (int r = 0; r < RPW; r++) {
                    const float cr = __shfl_sync(0xffffffffu, c, LPR * r + hw);
                    acc0 = fmaf(cr, (float)v[r].x, acc0);
                    acc1 = fmaf(cr, (float)v[r].y, acc1);
                    acc2 = fmaf(cr, (float)v[r].z, acc2);
                    acc3 = fmaf(cr, (float)v[r].w, acc3);
                }
            } while (nh == cur);

            float* red = reinterpret_cast<float*>(smem + OFF_RED) + (nflush & 1) * NCW * RED_STRIDE;
            float l = lsum + __shfl_xor_sync(0xffffffffu, lsum, 16);
            float z = zsum + __shfl_xor_sync(0xffffffffu, zsum, 16);
            if (RPW == 4) { l += __shfl_xor_sync(0xffffffffu, l, 8); z += __shfl_xor_sync(0xffffffffu, z, 8); }
            z = __shfl_sync(0xffffffffu, z, hw);
            *reinterpret_cast<float4*>(red + cw * RED_STRIDE + 4 * lane) = make_float4(acc0 - z, acc1 - z, acc2 - z, acc3 - z);
            if (lane == 0) *reinterpret_cast<float2*>(red + cw * RED_STRIDE + D) = make_float2(m, l);
            asm volatile("bar.sync 1, %0;" ::"n"(NCW * 32) : "memory");
            if (cw == (nflush & (NCW - 1))) {
                float2 ml[NCW]; float M = NEG_INF;
#pragma unroll
                for (int w = 0; w < NCW; w++) { ml[w] = *reinterpret_cast<const float2*>(red + w * RED_STRIDE + D); M = fmaxf(M, ml[w].x); }
                float4 a = make_float4(0, 0, 0, 0); float L = 0.f;
#pragma unroll
                for (int w = 0; w < NCW; w++) {
                    const float e = exp_diff(ml[w].x, M);
                    const float4 t = *reinterpret_cast<const float4*>(red + w * RED_STRIDE + 4 * lane);
                    a.x += e * t.x; a.y += e * t.y; a.z += e * t.z; a.w += e * t.w;
                    L += e * ml[w].y;
                }
                publish(cur, lane, a, M, L, tag);
                for (int e = cur + 1; e < nh; e++) publish(e, lane, make_float4(0, 0, 0, 0), NEG_INF, 0.f, tag);
                if (lane == 0) s_flushed = nh;
            }
            nflush++;
            if (nh >= H) break;
            cur = nh;
        }

        }
        const uint32_t wofs = (cw * RPI + lane / LR) * KPL;
        uint32_t wph = 0;
#pragma unroll 1
        for (int o = blockIdx.x; o < NOWN; o += nct) {
            float o0 = 0.f, o1 = 0.f, o2 = 0.f, o3 = 0.f;
            if (live) mbar_wait(smem_u32(&s_wbar), wph);
            wph ^= 1;
#pragma unroll 1
            for (int t = live ? 0 : NT - 1; t < NT; t++) {
                float c[KPL];
#pragma unroll
                for (int k = 0; k < KPL; k++) c[k] = reinterpret_cast<const float*>(smem + OFF_W)[t * TROWS + wofs + k];
                if (live) mbar_wait(smem_u32(&s_full[s]), ph);
                if (threadIdx.x == NTHREADS - 32 && t == NT - 1 && live) STAMP(7);
                int4 v[KPL];
#pragma unroll
                for (int k = 0; k < KPL; k++) v[k] = lds128(sbase + s * SLOT + (wofs + k) * (QW * 4) + (lane & (LR - 1)) * 16);
                __syncwarp();
                if (lane == 0 && live) mbar_arrive(smem_u32(&s_empty[s]));
                if (live && ++s == NST) { s = 0; ph ^= 1; }
#pragma unroll
                for (int k = 0; k < KPL; k++) {
                    o0 = fmaf(c[k], (float)v[k].x, o0); o1 = fmaf(c[k], (float)v[k].y, o1);
                    o2 = fmaf(c[k], (float)v[k].z, o2); o3 = fmaf(c[k], (float)v[k].w, o3);
                }
            }
            reduce_groups(reinterpret_cast<float*>(smem + OFF_TR) + cw * QW, o0, o1, o2, o3, lane);
            asm volatile("{ .reg .pred p; setp.ne.u32 p, %0, 0; @p bar.arrive 4, %1; }" ::"r"(live), "n"((NHW + NCW) * 32) : "memory");
        }
        if (live) break;
        }
    }
}

}
extern "C" void kernel_launch(void* const* d_in, const int* in_sizes, int n_in, void* d_out, int out_size) {
    typedef CUresult (*EncodeFn)(CUtensorMap*, CUtensorMapDataType, cuuint32_t, void*, const cuuint64_t*, const cuuint64_t*,
                                 const cuuint32_t*, const cuuint32_t*, CUtensorMapInterleave, CUtensorMapSwizzle,
                                 CUtensorMapL2promotion, CUtensorMapFloatOOBfill);
    static int nsm = 0;
    static EncodeFn encode = nullptr;
    if (nsm == 0) {
        int dev = 0;
        cudaGetDevice(&dev);
        cudaDeviceGetAttribute(&nsm, cudaDevAttrMultiProcessorCount, dev);
        if (nsm > MAXCTA) nsm = MAXCTA;
        cudaFuncSetAttribute(kv_decode_kernel, cudaFuncAttributeMaxDynamicSharedMemorySize, SMEM_BYTES);
        cudaDriverEntryPointQueryResult qr;
        cudaGetDriverEntryPoint("cuTensorMapEncodeTiled", (void**)&encode, cudaEnableDefault, &qr);
    }
    CUtensorMap vmap;
    const cuuint64_t gdim[2] = {(cuuint64_t)D, (cuuint64_t)H * S};
    const cuuint64_t gstr[1] = {(cuuint64_t)D * 4};
    const cuuint32_t box[2] = {(cuuint32_t)QW, (cuuint32_t)TROWS};
    const cuuint32_t estr[2] = {1, 1};
    encode(&vmap, CU_TENSOR_MAP_DATA_TYPE_INT32, 2, d_in[4], gdim, gstr, box, estr, CU_TENSOR_MAP_INTERLEAVE_NONE,
           CU_TENSOR_MAP_SWIZZLE_NONE, X_PROMO, CU_TENSOR_MAP_FLOAT_OOB_FILL_NONE);
    kv_decode_kernel<<<nsm, NTHREADS, SMEM_BYTES>>>(
        vmap, (const __nv_bfloat16*)d_in[0], (const int*)d_in[1], (const __nv_bfloat16*)d_in[2],
        (const __nv_bfloat16*)d_in[3], (const int*)d_in[4], (const __nv_bfloat16*)d_in[5],
        (const __nv_bfloat16*)d_in[6], (const __nv_bfloat16*)d_in[7], (const __nv_bfloat16*)d_in[8],
        (const __nv_bfloat16*)d_in[9], (const __nv_bfloat16*)d_in[10], (__nv_bfloat16*)d_out);
}
```

```cpp
#include <cuda_runtime.h>
#include <cuda.h>
#include <cuda_bf16.h>
#include <stdint.h>
#include <stddef.h>

#define KP 16
#define KNST 8
#define KQW 32
#define KNT 10
#define KTB 8192
#define KLIM 16
#define KLIMT 10
#define X_FREE 0
#define X_EARLY 0
#define X_B0 0
#define X_B1 0
#define X_W0 8448
#define X_BACKOFF 100
#define X_SLEEP 64
#define X_LAG 1
#define X_PROMO CU_TENSOR_MAP_L2_PROMOTION_NONE
#define NG 1
#define GW 8
#define NCW (NG * GW)
#define NHW 4
#define NTHREADS ((1 + NHW + NCW) * 32)

namespace {

constexpr int H = 32, S = 8192, D = 128;
constexpr int P = KP, NST = KNST;
constexpr int BPH = S / P;
constexpr int NITEMS = BPH * H;
constexpr int RPW = P / GW;
constexpr int MAXCTA = 144;
static_assert(RPW == 2 || RPW == 4, "rows per warp");

constexpr int QW = KQW, OPH = D / QW, NOWN = H * OPH;
constexpr int LR = QW / 4, RPI = 32 / LR;
constexpr uint32_t T_BYTES = KTB;
constexpr int NT = KNT, TROWS = T_BYTES / (QW * 4), R = NT * TROWS;
constexpr int KPL = T_BYTES / (NHW * 512);
constexpr int NQ = NCW / NHW;
constexpr uint32_t HK = R / P;
constexpr int HROWS = TROWS / NHW;
constexpr int NW = (NT * HROWS + 31) / 32;
constexpr int NJ = (MAXCTA + NHW * RPI - 1) / (NHW * RPI);
static_assert(R % P == 0 && R < S && NST <= 8 && KPL >= 1 && NST % NG == 0 && NST % NQ == 0, "held-back rows");

constexpr uint32_t KV_BYTES = P * D * 4;
constexpr uint32_t CS_BYTES = P * D * 2;
constexpr uint32_t SC_BYTES = P * 4;
constexpr uint32_t OFF_K = 0, OFF_V = KV_BYTES, OFF_C = 2 * KV_BYTES, OFF_S = OFF_C + CS_BYTES;
constexpr uint32_t OFF_KS = OFF_S + CS_BYTES, OFF_KZ = OFF_KS + SC_BYTES, OFF_VS = OFF_KZ + SC_BYTES,
                   OFF_VZ = OFF_VS + SC_BYTES;
constexpr uint32_t SLOT_TX = OFF_VZ + SC_BYTES;
constexpr uint32_t SLOT = (SLOT_TX + 127) / 128 * 128;
constexpr uint32_t OFF_Q = NST * SLOT;
constexpr uint32_t OFF_QC = OFF_Q + H * D * 2, OFF_QS = OFF_QC + D * 2;
constexpr uint32_t Q_TX = H * D * 2 + 2 * D * 2;
constexpr uint32_t OFF_RED = OFF_Q + Q_TX;
constexpr uint32_t RED_STRIDE = D + 4;
constexpr uint32_t OFF_W = OFF_RED + 2 * NCW * RED_STRIDE * 4;
constexpr uint32_t OFF_TR = OFF_W + R * 4;
constexpr uint32_t OFF_HB = OFF_TR + NCW * QW * 4;
constexpr uint32_t SMEM_BYTES = OFF_HB + 2 * NHW * QW * 4;

struct Scratch {
    float4 acc[H * MAXCTA * 32];
    float2 ml[H * MAXCTA];
    uint2 row[H * 2 * R];
    alignas(128) unsigned int ticket;
    alignas(128) unsigned int epoch;
};
__device__ Scratch g_scratch;
#define STAMP(i)

__device__ __forceinline__ uint32_t smem_u32(const void* p) { return (uint32_t)__cvta_generic_to_shared(p); }
__device__ __forceinline__ bool elect_one() {
    uint32_t p;
    asm volatile("{ .reg .pred p; elect.sync _|p, 0xffffffff; selp.u32 %0, 1, 0, p; }" : "=r"(p));
    return p;
}
__device__ __forceinline__ uint32_t opaque_zero() {
    uint32_t z;
    asm volatile("mov.u32 %0, 0;" : "=r"(z));
    return z;
}
__device__ __forceinline__ void mbar_init(uint32_t bar, uint32_t cnt) {
    asm volatile("mbarrier.init.shared.b64 [%0], %1;" ::"r"(bar), "r"(cnt) : "memory");
}
__device__ __forceinline__ void mbar_expect_tx(uint32_t bar, uint32_t bytes) {
    asm volatile("mbarrier.arrive.expect_tx.shared.b64 _, [%0], %1;" ::"r"(bar), "r"(bytes) : "memory");
}
__device__ __forceinline__ void mbar_arrive(uint32_t bar) {
    asm volatile("mbarrier.arrive.shared.b64 _, [%0];" ::"r"(bar) : "memory");
}
__device__ __forceinline__ void mbar_wait(uint32_t bar, uint32_t parity) {
    uint32_t done;
    int it = 0;
    do {
        asm volatile("{ .reg .pred p; mbarrier.try_wait.parity.shared.b64 p, [%1], %2; selp.u32 %0, 1, 0, p; }"
                     : "=r"(done) : "r"(bar), "r"(parity) : "memory");
        if (++it > (1 << 24)) __trap();
    } while (!done);
}
__device__ __forceinline__ void bulk_g2s(uint32_t dst, const void* src, uint32_t bytes, uint32_t bar) {
    asm volatile("cp.async.bulk.shared::cluster.global.mbarrier::complete_tx::bytes [%0], [%1], %2, [%3];"
                 ::"r"(dst), "l"(src), "r"(bytes), "r"(bar) : "memory");
}
__device__ __forceinline__ void bulk_g2s_hint(uint32_t dst, const void* src, uint32_t bytes, uint32_t bar, uint64_t pol) {
    asm volatile("cp.async.bulk.shared::cluster.global.mbarrier::complete_tx::bytes.L2::cache_hint [%0], [%1], %2, [%3], %4;"
                 ::"r"(dst), "l"(src), "r"(bytes), "r"(bar), "l"(pol) : "memory");
}
__device__ __forceinline__ int4 lds128(uint32_t a) {
    int4 v;
    asm volatile("ld.shared.v4.s32 {%0,%1,%2,%3}, [%4];" : "=r"(v.x), "=r"(v.y), "=r"(v.z), "=r"(v.w) : "r"(a));
    return v;
}
__device__ __forceinline__ uint2 lds64(uint32_t a) {
    uint2 v;
    asm volatile("ld.shared.v2.u32 {%0,%1}, [%2];" : "=r"(v.x), "=r"(v.y) : "r"(a));
    return v;
}
__device__ __forceinline__ uint32_t lds32(uint32_t a) {
    uint32_t v;
    asm volatile("ld.shared.u32 %0, [%1];" : "=r"(v) : "r"(a));
    return v;
}
__device__ __forceinline__ uint32_t lds16(uint32_t a) {
    uint16_t v;
    asm volatile("ld.shared.u16 %0, [%1];" : "=h"(v) : "r"(a));
    return v;
}
__device__ __forceinline__ uint32_t bf2_mul(uint32_t a, uint32_t b) {
    uint32_t d; asm("mul.rn.bf16x2 %0, %1, %2;" : "=r"(d) : "r"(a), "r"(b)); return d;
}
__device__ __forceinline__ uint32_t bf2_add(uint32_t a, uint32_t b) {
    uint32_t d; asm("add.rn.bf16x2 %0, %1, %2;" : "=r"(d) : "r"(a), "r"(b)); return d;
}
__device__ __forceinline__ uint32_t bf2_sub(uint32_t a, uint32_t b) {
    uint32_t d; asm("sub.rn.bf16x2 %0, %1, %2;" : "=r"(d) : "r"(a), "r"(b)); return d;
}
__device__ __forceinline__ uint32_t bf2_pack(float lo, float hi) {
    uint32_t d; asm("cvt.rn.bf16x2.f32 %0, %1, %2;" : "=r"(d) : "f"(hi), "f"(lo)); return d;
}
__device__ __forceinline__ float bf_lo(uint32_t v) { return __uint_as_float(v << 16); }
__device__ __forceinline__ float bf_hi(uint32_t v) { return __uint_as_float(v & 0xffff0000u); }
__device__ __forceinline__ float bf_round(float x) { return __bfloat162float(__float2bfloat16_rn(x)); }
__device__ __forceinline__ float ex2(float x) { float y; asm("ex2.approx.ftz.f32 %0, %1;" : "=f"(y) : "f"(x)); return y; }

constexpr float LOG2E = 1.4426950408889634f;
constexpr float NEG_INF = -__builtin_huge_valf();

__device__ __forceinline__ float exp_diff(float a, float b) {
    return (a == NEG_INF) ? 0.f : ex2((a - b) * LOG2E);
}

__device__ __forceinline__ uint32_t tagw(float x, uint32_t tag) { return (__float_as_uint(x) & ~1u) | tag; }
__device__ __forceinline__ float untag(uint32_t x) { return __uint_as_float(x & ~1u); }
__device__ __forceinline__ void publish(Scratch* sc, int h, int lane, float4 a, float M, float L, uint32_t tag) {
    float4* pa = sc->acc + (size_t)(h * MAXCTA + blockIdx.x) * 32 + lane;
    asm volatile("st.relaxed.gpu.global.v4.b32 [%0], {%1,%2,%3,%4};" ::"l"(pa), "r"(tagw(a.x, tag)), "r"(tagw(a.y, tag)),
                 "r"(tagw(a.z, tag)), "r"(tagw(a.w, tag)) : "memory");
    if (lane == 0)
        asm volatile("st.relaxed.gpu.global.v2.b32 [%0], {%1,%2};" ::"l"(sc->ml + h * MAXCTA + blockIdx.x),
                     "r"(tagw(M, tag)), "r"(tagw(L, tag)) : "memory");
}

__device__ __forceinline__ void reduce_groups(float* dst, float o0, float o1, float o2, float o3, int lane) {
    const bool hi = lane & 16;
    const float r0 = (hi ? o2 : o0) + __shfl_xor_sync(0xffffffffu, hi ? o0 : o2, 16);
    const float r1 = (hi ? o3 : o1) + __shfl_xor_sync(0xffffffffu, hi ? o1 : o3, 16);
    dst += (lane & (LR - 1)) * 4 + hi * 2;
    if (RPI == 4) {
        const bool up = lane & 8;
        dst[up] = (up ? r1 : r0) + __shfl_xor_sync(0xffffffffu, up ? r0 : r1, 8);
    } else {
        *reinterpret_cast<float2*>(dst) = make_float2(r0, r1);
    }
}

__device__ __forceinline__ uint32_t held0(uint32_t h) { return X_B0 + h * X_B1; }
constexpr uint32_t W0 = X_W0, LAST0 = (H - 1) * BPH + X_B0 + (H - 1) * X_B1;
__device__ __forceinline__ uint32_t item_index(uint32_t i) {
    return i - W0 < HK ? LAST0 + i - W0 : i - W0 < LAST0 + HK - W0 ? i - HK : i;
}
__device__ __forceinline__ uint32_t stream_head(uint32_t i) {
    return i - W0 < HK ? W0 / BPH : min(item_index(i) / BPH, (uint32_t)H);
}

__global__ void __launch_bounds__(NTHREADS, 1)
kv_decode_kernel(const int* __restrict__ qk, const int* __restrict__ qv,
                 const __nv_bfloat16* __restrict__ k_cos, const __nv_bfloat16* __restrict__ k_sin,
                 const __nv_bfloat16* __restrict__ ks, const __nv_bfloat16* __restrict__ kz,
                 const __nv_bfloat16* __restrict__ vs, const __nv_bfloat16* __restrict__ vz,
                 const __nv_bfloat16* __restrict__ q, const __nv_bfloat16* __restrict__ q_cos,
                 const __nv_bfloat16* __restrict__ q_sin, __nv_bfloat16* __restrict__ out, Scratch* __restrict__ sc,
                 const __grid_constant__ CUtensorMap vmap) {
    extern __shared__ __align__(128) unsigned char smem[];
    __shared__ __align__(8) uint64_t s_full[NST], s_empty[NST], s_qbar, s_wbar;
    __shared__ volatile int s_meta[NST];
    __shared__ volatile int s_flushed;
    __shared__ float4 s_hm[2][NHW];
    __shared__ uint32_t s_epoch;
    const int warp = __shfl_sync(0xffffffffu, threadIdx.x >> 5, 0), lane = threadIdx.x & 31;
    const uint32_t sbase = smem_u32(smem);
    const uint32_t nct = gridDim.x;
    constexpr int KU = KV_BYTES / 4096, NPRE = KLIM / (2 * KU);
    static_assert(NPRE >= 2 && W0 >= 2 * MAXCTA && MAXCTA <= BPH, "static items");
    uint64_t pol;
    asm volatile("createpolicy.fractional.L2::evict_first.b64 %0, 1.0;" : "=l"(pol));
    auto meta = [&](uint32_t idx, uint32_t nhead) {
        const uint32_t hb = (idx & (BPH - 1)) - held0(idx / BPH);
        return nhead | idx / BPH << 8 | (hb < HK ? (hb + 1) << 16 : 0);
    };
    auto issue = [&](int s, uint32_t idx) {
        const uint32_t blk = idx & (BPH - 1);
        const bool held = blk - held0(idx / BPH) < HK;
        const uint32_t bar = smem_u32(&s_full[s]), dst = sbase + s * SLOT;
        mbar_expect_tx(bar, held ? SLOT_TX - KV_BYTES : SLOT_TX);
        bulk_g2s_hint(dst + OFF_K, qk + (size_t)idx * (P * D), KV_BYTES, bar, pol);
        if (!held) bulk_g2s_hint(dst + OFF_V, qv + (size_t)idx * (P * D), KV_BYTES, bar, pol);
        bulk_g2s(dst + OFF_C, k_cos + blk * (P * D), CS_BYTES, bar);
        bulk_g2s(dst + OFF_S, k_sin + blk * (P * D), CS_BYTES, bar);
        bulk_g2s_hint(dst + OFF_KS, ks + idx * (P * 2), SC_BYTES, bar, pol);
        bulk_g2s_hint(dst + OFF_KZ, kz + idx * (P * 2), SC_BYTES, bar, pol);
        bulk_g2s_hint(dst + OFF_VS, vs + idx * (P * 2), SC_BYTES, bar, pol);
        bulk_g2s_hint(dst + OFF_VZ, vz + idx * (P * 2), SC_BYTES, bar, pol);
    };
    const bool leader = elect_one();
    const uint32_t tbase = (NPRE + 1) * nct, twrap = NITEMS - tbase + nct - 1;
    uint32_t epoch, pend;
    if (leader) {
        if (warp < NST) {
            mbar_init(smem_u32(&s_full[warp]), 1);
            asm volatile("fence.mbarrier_init.release.cluster;" ::: "memory");
            if (warp == 0) {
                issue(0, blockIdx.x);
                if (X_EARLY) asm volatile("atom.relaxed.gpu.global.inc.u32 %0, [%1], %2;" : "=r"(pend) : "l"(&sc->ticket), "r"(twrap) : "memory");
                s_meta[0] = meta(blockIdx.x, (blockIdx.x + nct) / BPH);
            }
            if (warp == 1) asm volatile("ld.relaxed.gpu.global.u32 %0, [%1];" : "=r"(epoch) : "l"(&sc->epoch) : "memory");
            mbar_init(smem_u32(&s_empty[warp]), NCW);
        } else if (warp == NST) {
            mbar_init(smem_u32(&s_qbar), 1);
            asm volatile("fence.mbarrier_init.release.cluster;" ::: "memory");
            mbar_expect_tx(smem_u32(&s_qbar), Q_TX);
            bulk_g2s(sbase + OFF_Q, q, H * D * 2, smem_u32(&s_qbar));
            bulk_g2s(sbase + OFF_QC, q_cos, D * 2, smem_u32(&s_qbar));
            bulk_g2s(sbase + OFF_QS, q_sin, D * 2, smem_u32(&s_qbar));
            mbar_init(smem_u32(&s_wbar), NHW);
        }
    }
    __syncthreads();

    if (warp == 0) {
        if (leader) {
            STAMP(15);
            int s = 1, ph = 1, cnt = 1;
            int ls = 0, lph = 0, fl = blockIdx.x - held0(0) < HK ? KU : 2 * KU, ret = NST;
            uint32_t cost = fl;
            uint32_t cur = blockIdx.x + nct, nxt = cur + nct;
#pragma unroll 1
            for (uint32_t live = opaque_zero();; live++) {
                do {
                    const uint32_t idx = item_index(cur);
                    const int c = (idx & (BPH - 1)) - held0(idx / BPH) < HK ? KU : 2 * KU;
                    fl += c;
                    while (fl > KLIM || (KLIM > NST * KU && cnt == ret)) {
                        mbar_wait(smem_u32(&s_full[ls]), lph);
                        fl -= (cost >> 4 * ls) & 15;
                        ret++;
                        if (++ls == NST) { ls = 0; lph ^= 1; }
                    }
                    if (cnt >= NST) mbar_wait(smem_u32(&s_empty[s]), ph);
                    cost = (cost & ~(15u << 4 * s)) | c << 4 * s;
                    s_meta[s] = meta(idx, stream_head(nxt));
                    issue(s, idx);
                    cnt++;
                    if (++s == NST) { s = 0; ph ^= 1; }
                    cur = nxt;
                    if (cur >= (uint32_t)NITEMS) break;
                    if (!X_EARLY && cnt == NPRE - 1)
                        asm volatile("atom.relaxed.gpu.global.inc.u32 %0, [%1], %2;" : "=r"(pend) : "l"(&sc->ticket), "r"(twrap) : "memory");
                    if (cnt < NPRE) { nxt += nct; continue; }
                    nxt = pend + tbase;
                    if (nxt < (uint32_t)NITEMS)
                        asm volatile("atom.relaxed.gpu.global.inc.u32 %0, [%1], %2;" : "=r"(pend) : "l"(&sc->ticket), "r"(twrap) : "memory");
                } while (live || cnt < NPRE);
                asm volatile("prefetch.tensormap [%0];" ::"l"(&vmap) : "memory");
#pragma unroll 1
                for (int o = blockIdx.x; o < NOWN; o += nct) {
#pragma unroll 1
                    for (int t = live ? 0 : NT - 1; t < NT; t++) {
                        if (live) {
                            fl += T_BYTES / 4096;
                            while ((fl > KLIMT && t < NT - X_FREE) || cnt == ret) {
                                mbar_wait(smem_u32(&s_full[ls]), lph);
                                fl -= (cost >> 4 * ls) & 15;
                        ret++;
                                if (++ls == NST) { ls = 0; lph ^= 1; }
                            }
                            mbar_wait(smem_u32(&s_empty[s]), ph);
                            cost = (cost & ~(15u << 4 * s)) | (T_BYTES / 4096) << 4 * s;
                            cnt++;
                        }
                        asm volatile("{ .reg .pred p; setp.ne.u32 p, %6, 0;\n"
                                     "@p mbarrier.arrive.expect_tx.shared.b64 _, [%2], %7;\n"
                                     "@p cp.async.bulk.tensor.2d.shared::cluster.global.mbarrier::complete_tx::bytes.L2::cache_hint "
                                     "[%0], [%1, {%3, %4}], [%2], %5; }" ::"r"(sbase + s * SLOT), "l"(&vmap), "r"(smem_u32(&s_full[s])),
                                     "r"((o % OPH) * QW), "r"((o / OPH) * S + held0(o / OPH) * P + t * TROWS), "l"(pol), "r"(live), "n"(T_BYTES) : "memory");
                        if (live && ++s == NST) { s = 0; ph ^= 1; }
                    }
                }
                if (live) break;
            }
        }
    } else if (warp <= NHW) {
        const int mw = warp - 1;
        if (warp == 1 && leader) { s_epoch = epoch; s_flushed = 0; }
        asm volatile("bar.sync 2, %0;" ::"n"(NTHREADS - 32) : "memory");
        const uint32_t tag = (s_epoch + 1) & 1;
        float* sw = reinterpret_cast<float*>(smem + OFF_W);
        const float* tr = reinterpret_cast<const float*>(smem + OFF_TR);
#pragma unroll 1
        for (int o = blockIdx.x; o < NOWN; o += nct) {
            const int h = o / OPH, col0 = (o % OPH) * QW;
            const uint2* pr = sc->row + (h * 2 + col0 / 64) * R + mw * HROWS;
            const int c0 = mw * RPI + lane / LR;
            const float4* pa = sc->acc + (size_t)(h * MAXCTA + c0) * 32 + col0 / 4 + (lane & (LR - 1));
            const float2* pm = sc->ml + h * MAXCTA + c0;
#pragma unroll 1
            for (uint32_t live = opaque_zero();; live++) {
                uint2 rw[NW];
                uint32_t bad = 0;
#pragma unroll
                for (int j = 0; j < NW; j++) {
                    rw[j] = make_uint2(0xff800000u, 0);
                    if (live && lane + 32 * j < NT * HROWS) bad |= 1u << j;
                }
                for (int k = 0; live && s_flushed <= (h == H - 1 ? min((int)(W0 / BPH) + 1, H - 2) : h); k++) { __nanosleep(X_SLEEP); if (k > (1 << 24)) __trap(); }
                for (int it = 0;; it++) {
#pragma unroll
                    for (int j = 0; j < NW; j++) {
                        const int i = lane + 32 * j;
                        asm volatile("{ .reg .pred p; .reg .b64 t; setp.ne.u32 p, %2, 0; mov.b64 t, {%0, %1};\n"
                                     "@p ld.relaxed.gpu.global.b64 t, [%3]; mov.b64 {%0, %1}, t; }"
                                     : "+r"(rw[j].x), "+r"(rw[j].y)
                                     : "r"(bad & (1u << j)), "l"(pr + i / HROWS * TROWS + i % HROWS) : "memory");
                    }
                    uint32_t nb = 0;
#pragma unroll
                    for (int j = NW - 1; j >= 0; j--) nb = nb * 2 + ((rw[j].x ^ tag) & 1);
                    bad &= nb;
                    if (!__any_sync(0xffffffffu, bad)) break;
                    __nanosleep(400);
                    if (it > (1 << 22)) __trap();
                }
                float Mr = NEG_INF, Lr = 0.f, Zr = 0.f;
#pragma unroll
                for (int j = 0; j < NW; j++) Mr = fmaxf(Mr, untag(rw[j].x));
#pragma unroll
                for (int x = 16; x > 0; x >>= 1) Mr = fmaxf(Mr, __shfl_xor_sync(0xffffffffu, Mr, x));
#pragma unroll
                for (int j = 0; j < NW; j++) {
                    const int i = lane + 32 * j;
                    const float p = exp_diff(untag(rw[j].x), Mr), w = p * bf_hi(rw[j].y);
                    Lr += p;
                    Zr = fmaf(w, bf_lo(rw[j].y), Zr);
                    if (i < NT * HROWS) sw[i / HROWS * TROWS + mw * HROWS + i % HROWS] = w;
                }
                __syncwarp();
                if (lane == 0 && live) mbar_arrive(smem_u32(&s_wbar));
#pragma unroll
                for (int x = 16; x > 0; x >>= 1) { Lr += __shfl_xor_sync(0xffffffffu, Lr, x); Zr += __shfl_xor_sync(0xffffffffu, Zr, x); }
                if (threadIdx.x == 32) STAMP(8);
                uint4 a[NJ]; uint2 ml[NJ];
#pragma unroll
                for (int j = 0; j < NJ; j++) {
                    a[j] = make_uint4(0, 0, 0, 0); ml[j] = make_uint2(0xff800000u, 0);
                    if (live && c0 + NHW * RPI * j < nct) bad |= 1u << j;
                }
                for (int k = 0; live && s_flushed <= min(h + X_LAG, H - 1); k++) { __nanosleep(X_SLEEP); if (k > (1 << 24)) __trap(); }
                if (threadIdx.x == 32) STAMP(9);
                for (int it = 0;; it++) {
#pragma unroll
                    for (int j = 0; j < NJ; j++) {
                        asm volatile("{ .reg .pred p; setp.ne.u32 p, %6, 0;\n"
                                     "@p ld.relaxed.gpu.global.v4.b32 {%0,%1,%2,%3}, [%7];\n"
                                     "@p ld.relaxed.gpu.global.v2.b32 {%4,%5}, [%8]; }"
                                     : "+r"(a[j].x), "+r"(a[j].y), "+r"(a[j].z), "+r"(a[j].w), "+r"(ml[j].x), "+r"(ml[j].y)
                                     : "r"(bad & (1u << j)), "l"(pa + NHW * RPI * 32 * j), "l"(pm + NHW * RPI * j) : "memory");
                    }
                    uint32_t nb = 0;
#pragma unroll
                    for (int j = NJ - 1; j >= 0; j--) {
                        uint32_t x;
                        asm volatile("{ .reg .b32 u, v;\n"
                            "lop3.b32 u, %1, %2, %7, 0x7e;\n lop3.b32 v, %3, %4, %7, 0x7e;\n lop3.b32 %0, %5, %6, %7, 0x7e;\n"
                            "lop3.b32 %0, %0, u, v, 0xfe; }"
                            : "=r"(x) : "r"(a[j].x), "r"(a[j].y), "r"(a[j].z), "r"(a[j].w), "r"(ml[j].x), "r"(ml[j].y), "r"(tag));
                        nb = nb * 2 + (x & 1);
                    }
                    bad &= nb;
                    if (!__any_sync(0xffffffffu, bad)) break;
                    if (X_BACKOFF) __nanosleep(X_BACKOFF);
                    if (it > (1 << 22)) __trap();
                }
                if (lane == 0) STAMP(10 + mw);
                float M = Mr;
#pragma unroll
                for (int j = 0; j < NJ; j++) M = fmaxf(M, untag(ml[j].x));
#pragma unroll
                for (int x = 16; x >= LR; x >>= 1) M = fmaxf(M, __shfl_xor_sync(0xffffffffu, M, x));
                const float fr = exp_diff(Mr, M);
                float o0 = 0.f, o1 = 0.f, o2 = 0.f, o3 = 0.f, L = 0.f;
#pragma unroll
                for (int j = 0; j < NJ; j++) {
                    const float e = exp_diff(untag(ml[j].x), M);
                    o0 = fmaf(e, untag(a[j].x), o0); o1 = fmaf(e, untag(a[j].y), o1);
                    o2 = fmaf(e, untag(a[j].z), o2); o3 = fmaf(e, untag(a[j].w), o3);
                    L = fmaf(e, untag(ml[j].y), L);
                }
                float* hb = reinterpret_cast<float*>(smem + OFF_HB) + live * NHW * QW;
                reduce_groups(hb + mw * QW, o0, o1, o2, o3, lane);
#pragma unroll
                for (int x = 16; x >= LR; x >>= 1) L += __shfl_xor_sync(0xffffffffu, L, x);
                if (lane == 0) s_hm[live][mw] = make_float4(M, fmaf(fr, Lr, L), fr, fr * Zr);
                asm volatile("bar.sync 3, %0;" ::"n"(NHW * 32) : "memory");
                float MM = NEG_INF, LL = 0.f, base = 0.f, g[NHW];
                const int col = (mw * 32 + lane) & (QW - 1);
#pragma unroll
                for (int w = 0; w < NHW; w++) MM = fmaxf(MM, s_hm[live][w].x);
#pragma unroll
                for (int w = 0; w < NHW; w++) {
                    const float4 x = s_hm[live][w];
                    const float e = exp_diff(x.x, MM);
                    LL = fmaf(e, x.y, LL);
                    base = fmaf(e, hb[w * QW + col] - x.w, base);
                    g[w] = e * x.z;
                }
                const float inv = __frcp_rn(LL);
                base *= inv;
#pragma unroll
                for (int w = 0; w < NHW; w++) g[w] *= inv;
                if (threadIdx.x == 32 && live) STAMP(5);
                asm volatile("{ .reg .pred p; setp.ne.u32 p, %0, 0; @p bar.sync 4, %1; }" ::"r"(live), "n"((NHW + NCW) * 32) : "memory");
#pragma unroll
                for (int w = 0; w < NHW; w++) {
                    float y = tr[w * QW + col];
                    if (NQ == 4) y = (y + tr[(NHW + w) * QW + col]) + (tr[(2 * NHW + w) * QW + col] + tr[(3 * NHW + w) * QW + col]);
                    else y += tr[(NHW + w) * QW + col];
                    g[w] *= y;
                }
                float y = base;
#pragma unroll
                for (int w = 0; w < NHW; w += 2) y += g[w] + g[w + 1];
                if (live && mw < QW / 32) out[h * D + col0 + col] = __float2bfloat16_rn(y);
                if (live) break;
            }
            if (o == NOWN - 1 && threadIdx.x == 32) sc->epoch = s_epoch + 1;
        }
        if (threadIdx.x == 32) STAMP(6);
    } else {
        const int cw = warp - 1 - NHW;
        const int hw = lane >> 4, li = lane & 15;
        int s = 0, ph = 0;
#pragma unroll 1
        for (uint32_t live = opaque_zero();; live++) {
        if (live) {
        asm volatile("bar.sync 2, %0;" ::"n"(NTHREADS - 32) : "memory");
        const uint32_t tag = (s_epoch + 1) & 1;
        mbar_wait(smem_u32(&s_qbar), 0);
        if (threadIdx.x == NTHREADS - 32) STAMP(1);
        int cur = stream_head(blockIdx.x), nflush = 0, qh = -1;
        if (cw == 0) for (int e = 0; e < cur; e++) publish(sc, e, lane, make_float4(0, 0, 0, 0), NEG_INF, 0.f, tag);
        float4 qlo, qhi;
        while (true) {
            float m = NEG_INF, lsum = 0.f, zsum = 0.f;
            float acc0 = 0.f, acc1 = 0.f, acc2 = 0.f, acc3 = 0.f;
            int nh;
            do {
                mbar_wait(smem_u32(&s_full[s]), ph);
                const int meta = s_meta[s];
                nh = meta & 255;
                if (NG > 1 && (s & (NG - 1)) != cw / GW) {
                    __syncwarp();
                    if (lane == 0) mbar_arrive(smem_u32(&s_empty[s]));
                    if (++s == NST) { s = 0; ph ^= 1; }
                    continue;
                }
                if (((meta >> 8) & 255) != qh) {
                    qh = (meta >> 8) & 255;
                    const uint2 l = lds64(sbase + OFF_Q + qh * 256 + li * 8), h = lds64(sbase + OFF_Q + qh * 256 + 128 + li * 8);
                    const uint2 cl = lds64(sbase + OFF_QC + li * 8), ch = lds64(sbase + OFF_QC + 128 + li * 8);
                    const uint2 sl = lds64(sbase + OFF_QS + li * 8), sh = lds64(sbase + OFF_QS + 128 + li * 8);
                    const uint32_t rl0 = bf2_sub(bf2_mul(l.x, cl.x), bf2_mul(h.x, sl.x));
                    const uint32_t rl1 = bf2_sub(bf2_mul(l.y, cl.y), bf2_mul(h.y, sl.y));
                    const uint32_t rh0 = bf2_add(bf2_mul(h.x, ch.x), bf2_mul(l.x, sh.x));
                    const uint32_t rh1 = bf2_add(bf2_mul(h.y, ch.y), bf2_mul(l.y, sh.y));
                    qlo = make_float4(bf_lo(rl0), bf_hi(rl0), bf_lo(rl1), bf_hi(rl1));
                    qhi = make_float4(bf_lo(rh0), bf_hi(rh0), bf_lo(rh1), bf_hi(rh1));
                }
                const uint32_t slot = sbase + s * SLOT;
                const int row0 = (cw & (GW - 1)) * RPW;
                float dot[RPW / 2];
#pragma unroll
                for (int it = 0; it < RPW / 2; it++) {
                    const int row = row0 + (RPW / 2) * hw + it;
                    const int4 a = lds128(slot + OFF_K + row * 512 + li * 16);
                    const int4 b = lds128(slot + OFF_K + row * 512 + 256 + li * 16);
                    const uint2 cl = lds64(slot + OFF_C + row * 256 + li * 8);
                    const uint2 ch = lds64(slot + OFF_C + row * 256 + 128 + li * 8);
                    const uint2 sl = lds64(slot + OFF_S + row * 256 + li * 8);
                    const uint2 sh = lds64(slot + OFF_S + row * 256 + 128 + li * 8);
                    const uint32_t sc = lds32(slot + OFF_KS + row * 4);
                    const uint32_t zc = lds32(slot + OFF_KZ + row * 4);
                    const uint32_t s0 = __byte_perm(sc, 0, 0x1010), s1 = __byte_perm(sc, 0, 0x3232);
                    const uint32_t z0 = __byte_perm(zc, 0, 0x1010), z1 = __byte_perm(zc, 0, 0x3232);
                    const uint32_t l0 = bf2_mul(bf2_sub(bf2_pack((float)a.x, (float)a.y), z0), s0);
                    const uint32_t l1 = bf2_mul(bf2_sub(bf2_pack((float)a.z, (float)a.w), z0), s0);
                    const uint32_t h0 = bf2_mul(bf2_sub(bf2_pack((float)b.x, (float)b.y), z1), s1);
                    const uint32_t h1 = bf2_mul(bf2_sub(bf2_pack((float)b.z, (float)b.w), z1), s1);
                    const uint32_t rl0 = bf2_sub(bf2_mul(l0, cl.x), bf2_mul(h0, sl.x));
                    const uint32_t rl1 = bf2_sub(bf2_mul(l1, cl.y), bf2_mul(h1, sl.y));
                    const uint32_t rh0 = bf2_add(bf2_mul(h0, ch.x), bf2_mul(l0, sh.x));
                    const uint32_t rh1 = bf2_add(bf2_mul(h1, ch.y), bf2_mul(l1, sh.y));
                    float d0 = qlo.x * bf_lo(rl0), d1 = qhi.x * bf_lo(rh0);
                    float d2 = qlo.z * bf_lo(rl1), d3 = qhi.z * bf_lo(rh1);
                    d0 = fmaf(qlo.y, bf_hi(rl0), d0); d1 = fmaf(qhi.y, bf_hi(rh0), d1);
                    d2 = fmaf(qlo.w, bf_hi(rl1), d2); d3 = fmaf(qhi.w, bf_hi(rh1), d3);
                    dot[it] = (d0 + d1) + (d2 + d3);
                }
                int4 v[RPW];
#pragma unroll
                for (int r = 0; r < RPW; r++) v[r] = lds128(slot + OFF_V + (row0 + r) * 512 + lane * 16);
                constexpr int LPR = 32 / RPW;
                const int myrow = row0 + lane / LPR;
                const uint32_t vsb = lds16(slot + OFF_VS + myrow * 4 + (lane & 1) * 2);
                const uint32_t vzb = lds16(slot + OFF_VZ + myrow * 4 + (lane & 1) * 2);
                const float vsc = __uint_as_float(vsb << 16), vzc = __uint_as_float(vzb << 16);
                __syncwarp();
                if (lane == 0) mbar_arrive(smem_u32(&s_empty[s]));
                if (++s == NST) { s = 0; ph ^= 1; }
                float t;
                if (RPW == 4) {
                    const bool up = lane & 8;
                    t = (up ? dot[RPW / 2 - 1] : dot[0]) + __shfl_xor_sync(0xffffffffu, up ? dot[0] : dot[RPW / 2 - 1], 8);
                } else {
                    t = dot[0] + __shfl_xor_sync(0xffffffffu, dot[0], 8);
                }
                t += __shfl_xor_sync(0xffffffffu, t, 4);
                t += __shfl_xor_sync(0xffffffffu, t, 2);
                t += __shfl_xor_sync(0xffffffffu, t, 1);
                const float lg = bf_round(bf_round(t) * 0.08838834764831845f);
                if (meta >> 16) {
                    if ((lane & (LPR - 1)) < 2)
                        asm volatile("{ .reg .b64 t; mov.b64 t, {%1, %2}; st.relaxed.gpu.global.b64 [%0], t; }"
                                     ::"l"(sc->row + (qh * 2 + (lane & 1)) * R + ((meta >> 16) - 1) * P + myrow),
                                     "r"(__float_as_uint(lg) | tag), "r"(vsb << 16 | vzb) : "memory");
                    continue;
                }
                float mx = fmaxf(lg, __shfl_xor_sync(0xffffffffu, lg, 16));
                if (RPW == 4) mx = fmaxf(mx, __shfl_xor_sync(0xffffffffu, mx, 8));
                const float mn = fmaxf(m, mx);
                const float alpha = exp_diff(m, mn);
                const float p = exp_diff(lg, mn);
                m = mn;
                const float c = p * vsc;
                lsum = fmaf(lsum, alpha, p);
                zsum = fmaf(zsum, alpha, c * vzc);
                acc0 *= alpha; acc1 *= alpha; acc2 *= alpha; acc3 *= alpha;
#pragma unroll
                for (int r = 0; r < RPW; r++) {
                    const float cr = __shfl_sync(0xffffffffu, c, LPR * r + hw);
                    acc0 = fmaf(cr, (float)v[r].x, acc0);
                    acc1 = fmaf(cr, (float)v[r].y, acc1);
                    acc2 = fmaf(cr, (float)v[r].z, acc2);
                    acc3 = fmaf(cr, (float)v[r].w, acc3);
                }
            } while (nh == cur);

            float* red = reinterpret_cast<float*>(smem + OFF_RED) + (nflush & 1) * NCW * RED_STRIDE;
            float l = lsum + __shfl_xor_sync(0xffffffffu, lsum, 16);
            float z = zsum + __shfl_xor_sync(0xffffffffu, zsum, 16);
            if (RPW == 4) { l += __shfl_xor_sync(0xffffffffu, l, 8); z += __shfl_xor_sync(0xffffffffu, z, 8); }
            z = __shfl_sync(0xffffffffu, z, hw);
            *reinterpret_cast<float4*>(red + cw * RED_STRIDE + 4 * lane) = make_float4(acc0 - z, acc1 - z, acc2 - z, acc3 - z);
            if (lane == 0) *reinterpret_cast<float2*>(red + cw * RED_STRIDE + D) = make_float2(m, l);
            asm volatile("bar.sync 1, %0;" ::"n"(NCW * 32) : "memory");
            if (cw == (nflush & (NCW - 1))) {
                float2 ml[NCW]; float M = NEG_INF;
#pragma unroll
                for (int w = 0; w < NCW; w++) { ml[w] = *reinterpret_cast<const float2*>(red + w * RED_STRIDE + D); M = fmaxf(M, ml[w].x); }
                float4 a = make_float4(0, 0, 0, 0); float L = 0.f;
#pragma unroll
                for (int w = 0; w < NCW; w++) {
                    const float e = exp_diff(ml[w].x, M);
                    const float4 t = *reinterpret_cast<const float4*>(red + w * RED_STRIDE + 4 * lane);
                    a.x += e * t.x; a.y += e * t.y; a.z += e * t.z; a.w += e * t.w;
                    L += e * ml[w].y;
                }
                publish(sc, cur, lane, a, M, L, tag);
                for (int e = cur + 1; e < nh; e++) publish(sc, e, lane, make_float4(0, 0, 0, 0), NEG_INF, 0.f, tag);
                if (lane == 0) s_flushed = nh;
            }
            nflush++;
            if (nh >= H) break;
            cur = nh;
        }

        }
        const uint32_t wofs = ((cw & (NHW - 1)) * RPI + lane / LR) * KPL;
        uint32_t wph = 0;
#pragma unroll 1
        for (int o = blockIdx.x; o < NOWN; o += nct) {
            float o0 = 0.f, o1 = 0.f, o2 = 0.f, o3 = 0.f;
            if (live) mbar_wait(smem_u32(&s_wbar), wph);
            wph ^= 1;
#pragma unroll 1
            for (int t = live ? (cw / NHW - s) & (NQ - 1) : NT - 1; t < NT; t += NQ) {
                float c[KPL];
#pragma unroll
                for (int k = 0; k < KPL; k++) c[k] = reinterpret_cast<const float*>(smem + OFF_W)[t * TROWS + wofs + k];
                const int ts = (s + t) % NST;
                if (live) mbar_wait(smem_u32(&s_full[ts]), ph ^ ((s + t) / NST & 1));
                if (lane == 0 && (cw & (NHW - 1)) == 0 && t == NT - 1 && live) STAMP(7);
                int4 v[KPL];
#pragma unroll
                for (int k = 0; k < KPL; k++) v[k] = lds128(sbase + ts * SLOT + (wofs + k) * (QW * 4) + (lane & (LR - 1)) * 16);
                __syncwarp();
                if (lane == 0 && live)
                    asm volatile("mbarrier.arrive.shared.b64 _, [%0], %1;" ::"r"(smem_u32(&s_empty[ts])), "n"(NQ) : "memory");
#pragma unroll
                for (int k = 0; k < KPL; k++) {
                    o0 = fmaf(c[k], (float)v[k].x, o0); o1 = fmaf(c[k], (float)v[k].y, o1);
                    o2 = fmaf(c[k], (float)v[k].z, o2); o3 = fmaf(c[k], (float)v[k].w, o3);
                }
            }
            if (live) { ph ^= (s + NT) / NST & 1; s = (s + NT) % NST; }
            reduce_groups(reinterpret_cast<float*>(smem + OFF_TR) + cw * QW, o0, o1, o2, o3, lane);
            asm volatile("{ .reg .pred p; setp.ne.u32 p, %0, 0; @p bar.arrive 4, %1; }" ::"r"(live), "n"((NHW + NCW) * 32) : "memory");
        }
        if (live) break;
        }
    }
}

}
extern "C" void kernel_launch(void* const* d_in, const int* in_sizes, int n_in, void* d_out, int out_size) {
    typedef CUresult (*EncodeFn)(CUtensorMap*, CUtensorMapDataType, cuuint32_t, void*, const cuuint64_t*, const cuuint64_t*,
                                 const cuuint32_t*, const cuuint32_t*, CUtensorMapInterleave, CUtensorMapSwizzle,
                                 CUtensorMapL2promotion, CUtensorMapFloatOOBfill);
    static int nsm = 0;
    static EncodeFn encode = nullptr;
    static Scratch* sc = nullptr;
    if (nsm == 0) {
        int dev = 0;
        cudaGetDevice(&dev);
        cudaDeviceGetAttribute(&nsm, cudaDevAttrMultiProcessorCount, dev);
        if (nsm > MAXCTA) nsm = MAXCTA;
        cudaFuncSetAttribute(kv_decode_kernel, cudaFuncAttributeMaxDynamicSharedMemorySize, SMEM_BYTES);
        cudaGetSymbolAddress((void**)&sc, g_scratch);
        cudaDriverEntryPointQueryResult qr;
        cudaGetDriverEntryPoint("cuTensorMapEncodeTiled", (void**)&encode, cudaEnableDefault, &qr);
    }
    CUtensorMap vmap;
    const cuuint64_t gdim[2] = {(cuuint64_t)D, (cuuint64_t)H * S};
    const cuuint64_t gstr[1] = {(cuuint64_t)D * 4};
    const cuuint32_t box[2] = {(cuuint32_t)QW, (cuuint32_t)TROWS};
    const cuuint32_t estr[2] = {1, 1};
    encode(&vmap, CU_TENSOR_MAP_DATA_TYPE_INT32, 2, d_in[4], gdim, gstr, box, estr, CU_TENSOR_MAP_INTERLEAVE_NONE,
           CU_TENSOR_MAP_SWIZZLE_NONE, X_PROMO, CU_TENSOR_MAP_FLOAT_OOB_FILL_NONE);
    kv_decode_kernel<<<nsm, NTHREADS, SMEM_BYTES>>>(
        (const int*)d_in[1], (const int*)d_in[4], (const __nv_bfloat16*)d_in[9], (const __nv_bfloat16*)d_in[10],
        (const __nv_bfloat16*)d_in[2], (const __nv_bfloat16*)d_in[3], (const __nv_bfloat16*)d_in[5],
        (const __nv_bfloat16*)d_in[6], (const __nv_bfloat16*)d_in[0], (const __nv_bfloat16*)d_in[7],
        (const __nv_bfloat16*)d_in[8], (__nv_bfloat16*)d_out, sc, vmap);
}
```

```cpp
#include <cuda_runtime.h>
#include <cuda.h>
#include <cuda_bf16.h>
#include <stdint.h>
#include <stddef.h>

#define KP 16
#define KNST 8
#define KQW 32
#define KNT 16
#define KTB 8192
#define KLIM 12
#define KLIMT 10
#define X_FREE 3
#define X_PACE 2
#define X_PA 90
#define X_PB 100
#define X_PC 100
#define X_BURST 1
#define X_STAT 0
#define X_EARLY 1
#define X_B0 124
#define X_B1 -4
#define X_W0 8448
#define X_BACKOFF 100
#define X_SLEEP 64
#define X_LAG 1
#define X_PROMO CU_TENSOR_MAP_L2_PROMOTION_NONE
#define X_SPF 64
#define X_SPA 1024
#define NG 1
#define GW 8
#define NCW (NG * GW)
#define NHW 4
#define NTHREADS ((1 + NHW + NCW) * 32)

namespace {

constexpr int H = 32, S = 8192, D = 128;
constexpr int P = KP, NST = KNST;
constexpr int BPH = S / P;
constexpr int NITEMS = BPH * H;
constexpr int RPW = P / GW;
constexpr int MAXCTA = 144;
static_assert(RPW == 2 || RPW == 4, "rows per warp");

constexpr int QW = KQW, OPH = D / QW, NOWN = H * OPH;
constexpr int LR = QW / 4, RPI = 32 / LR;
constexpr uint32_t T_BYTES = KTB;
constexpr int NT = KNT, TROWS = T_BYTES / (QW * 4), R = NT * TROWS;
constexpr int KPL = T_BYTES / (NHW * 512);
constexpr int NQ = NCW / NHW;
constexpr uint32_t HK = R / P;
constexpr int HROWS = TROWS / NHW;
constexpr int NW = (NT * HROWS + 31) / 32;
constexpr int NJ = (MAXCTA + NHW * RPI - 1) / (NHW * RPI);
static_assert(R % P == 0 && R < S && NST <= 8 && KPL >= 1 && NST % NG == 0 && NST % NQ == 0, "held-back rows");

constexpr uint32_t KV_BYTES = P * D * 4;
constexpr uint32_t CS_BYTES = P * D * 2;
constexpr uint32_t SC_BYTES = P * 4;
constexpr uint32_t OFF_K = 0, OFF_V = KV_BYTES, OFF_C = 2 * KV_BYTES, OFF_S = OFF_C + CS_BYTES;
constexpr uint32_t OFF_KS = OFF_S + CS_BYTES, OFF_KZ = OFF_KS + SC_BYTES, OFF_VS = OFF_KZ + SC_BYTES,
                   OFF_VZ = OFF_VS + SC_BYTES;
constexpr uint32_t SLOT_TX = OFF_VZ + SC_BYTES;
constexpr uint32_t SLOT = (SLOT_TX + 127) / 128 * 128;
constexpr uint32_t OFF_Q = NST * SLOT;
constexpr uint32_t OFF_QC = OFF_Q + H * D * 2, OFF_QS = OFF_QC + D * 2;
constexpr uint32_t Q_TX = H * D * 2 + 2 * D * 2;
constexpr uint32_t OFF_RED = OFF_Q + Q_TX;
constexpr uint32_t RED_STRIDE = D + 4;
constexpr uint32_t OFF_W = OFF_RED + 2 * NCW * RED_STRIDE * 4;
constexpr uint32_t OFF_TR = OFF_W + R * 4;
constexpr uint32_t OFF_HB = OFF_TR + NCW * QW * 4;
constexpr uint32_t SMEM_BYTES = OFF_HB + 2 * NHW * QW * 4;

struct Scratch {
    float4 acc[H * MAXCTA * 32];
    float2 ml[H * MAXCTA];
    uint2 row[H * 2 * R];
    alignas(128) unsigned int ticket;
    alignas(128) unsigned int epoch;
};
__device__ Scratch g_scratch;
#define STAMP(i)

__device__ __forceinline__ uint32_t smem_u32(const void* p) { return (uint32_t)__cvta_generic_to_shared(p); }
__device__ __forceinline__ bool elect_one() {
    uint32_t p;
    asm volatile("{ .reg .pred p; elect.sync _|p, 0xffffffff; selp.u32 %0, 1, 0, p; }" : "=r"(p));
    return p;
}
__device__ __forceinline__ uint32_t opaque_zero() {
    uint32_t z;
    asm volatile("mov.u32 %0, 0;" : "=r"(z));
    return z;
}
__device__ __forceinline__ uint32_t clock32() {
    uint32_t c;
    asm volatile("mov.u32 %0, %clock;" : "=r"(c));
    return c;
}
__device__ __forceinline__ void mbar_init(uint32_t bar, uint32_t cnt) {
    asm volatile("mbarrier.init.shared.b64 [%0], %1;" ::"r"(bar), "r"(cnt) : "memory");
}
__device__ __forceinline__ void mbar_expect_tx(uint32_t bar, uint32_t bytes) {
    asm volatile("mbarrier.arrive.expect_tx.shared.b64 _, [%0], %1;" ::"r"(bar), "r"(bytes) : "memory");
}
__device__ __forceinline__ void mbar_arrive(uint32_t bar) {
    asm volatile("mbarrier.arrive.shared.b64 _, [%0];" ::"r"(bar) : "memory");
}
__device__ __forceinline__ void mbar_wait(uint32_t bar, uint32_t parity) {
    uint32_t done;
    int it = 0;
    do {
        asm volatile("{ .reg .pred p; mbarrier.try_wait.parity.shared.b64 p, [%1], %2; selp.u32 %0, 1, 0, p; }"
                     : "=r"(done) : "r"(bar), "r"(parity) : "memory");
        if (++it > (1 << 24)) __trap();
    } while (!done);
}
__device__ __forceinline__ void bulk_g2s(uint32_t dst, const void* src, uint32_t bytes, uint32_t bar) {
    asm volatile("cp.async.bulk.shared::cluster.global.mbarrier::complete_tx::bytes [%0], [%1], %2, [%3];"
                 ::"r"(dst), "l"(src), "r"(bytes), "r"(bar) : "memory");
}
__device__ __forceinline__ void bulk_g2s_hint(uint32_t dst, const void* src, uint32_t bytes, uint32_t bar, uint64_t pol) {
    asm volatile("cp.async.bulk.shared::cluster.global.mbarrier::complete_tx::bytes.L2::cache_hint [%0], [%1], %2, [%3], %4;"
                 ::"r"(dst), "l"(src), "r"(bytes), "r"(bar), "l"(pol) : "memory");
}
__device__ __forceinline__ int4 lds128(uint32_t a) {
    int4 v;
    asm volatile("ld.shared.v4.s32 {%0,%1,%2,%3}, [%4];" : "=r"(v.x), "=r"(v.y), "=r"(v.z), "=r"(v.w) : "r"(a));
    return v;
}
__device__ __forceinline__ uint2 lds64(uint32_t a) {
    uint2 v;
    asm volatile("ld.shared.v2.u32 {%0,%1}, [%2];" : "=r"(v.x), "=r"(v.y) : "r"(a));
    return v;
}
__device__ __forceinline__ uint32_t lds32(uint32_t a) {
    uint32_t v;
    asm volatile("ld.shared.u32 %0, [%1];" : "=r"(v) : "r"(a));
    return v;
}
__device__ __forceinline__ uint32_t lds16(uint32_t a) {
    uint16_t v;
    asm volatile("ld.shared.u16 %0, [%1];" : "=h"(v) : "r"(a));
    return v;
}
__device__ __forceinline__ uint32_t bf2_mul(uint32_t a, uint32_t b) {
    uint32_t d; asm("mul.rn.bf16x2 %0, %1, %2;" : "=r"(d) : "r"(a), "r"(b)); return d;
}
__device__ __forceinline__ uint32_t bf2_add(uint32_t a, uint32_t b) {
    uint32_t d; asm("add.rn.bf16x2 %0, %1, %2;" : "=r"(d) : "r"(a), "r"(b)); return d;
}
__device__ __forceinline__ uint32_t bf2_sub(uint32_t a, uint32_t b) {
    uint32_t d; asm("sub.rn.bf16x2 %0, %1, %2;" : "=r"(d) : "r"(a), "r"(b)); return d;
}
__device__ __forceinline__ uint32_t bf2_pack(float lo, float hi) {
    uint32_t d; asm("cvt.rn.bf16x2.f32 %0, %1, %2;" : "=r"(d) : "f"(hi), "f"(lo)); return d;
}
__device__ __forceinline__ float bf_lo(uint32_t v) { return __uint_as_float(v << 16); }
__device__ __forceinline__ float bf_hi(uint32_t v) { return __uint_as_float(v & 0xffff0000u); }
__device__ __forceinline__ float bf_round(float x) { return __bfloat162float(__float2bfloat16_rn(x)); }
__device__ __forceinline__ float ex2(float x) { float y; asm("ex2.approx.ftz.f32 %0, %1;" : "=f"(y) : "f"(x)); return y; }

constexpr float LOG2E = 1.4426950408889634f;
constexpr float NEG_INF = -__builtin_huge_valf();

__device__ __forceinline__ float exp_diff(float a, float b) {
    return (a == NEG_INF) ? 0.f : ex2((a - b) * LOG2E);
}

__device__ __forceinline__ uint32_t tagw(float x, uint32_t tag) { return (__float_as_uint(x) & ~1u) | tag; }
__device__ __forceinline__ float untag(uint32_t x) { return __uint_as_float(x & ~1u); }
__device__ __forceinline__ void publish(Scratch* sc, int h, int lane, float4 a, float M, float L, uint32_t tag) {
    float4* pa = sc->acc + (size_t)(h * MAXCTA + blockIdx.x) * 32 + lane;
    asm volatile("st.relaxed.gpu.global.v4.b32 [%0], {%1,%2,%3,%4};" ::"l"(pa), "r"(tagw(a.x, tag)), "r"(tagw(a.y, tag)),
                 "r"(tagw(a.z, tag)), "r"(tagw(a.w, tag)) : "memory");
    if (lane == 0)
        asm volatile("st.relaxed.gpu.global.v2.b32 [%0], {%1,%2};" ::"l"(sc->ml + h * MAXCTA + blockIdx.x),
                     "r"(tagw(M, tag)), "r"(tagw(L, tag)) : "memory");
}

__device__ __forceinline__ void reduce_groups(float* dst, float o0, float o1, float o2, float o3, int lane) {
    const bool hi = lane & 16;
    const float r0 = (hi ? o2 : o0) + __shfl_xor_sync(0xffffffffu, hi ? o0 : o2, 16);
    const float r1 = (hi ? o3 : o1) + __shfl_xor_sync(0xffffffffu, hi ? o1 : o3, 16);
    dst += (lane & (LR - 1)) * 4 + hi * 2;
    if (RPI == 4) {
        const bool up = lane & 8;
        dst[up] = (up ? r1 : r0) + __shfl_xor_sync(0xffffffffu, up ? r0 : r1, 8);
    } else {
        *reinterpret_cast<float2*>(dst) = make_float2(r0, r1);
    }
}

__device__ __forceinline__ uint32_t held0(uint32_t h) { return X_B0 + (int)h * (X_B1); }
constexpr uint32_t W0 = X_W0, LAST0 = (H - 1) * BPH + X_B0 + (H - 1) * (X_B1);
__device__ __forceinline__ uint32_t item_index(uint32_t i) {
    return i - W0 < HK ? LAST0 + i - W0 : i - W0 < LAST0 + HK - W0 ? i - HK : i;
}
__device__ __forceinline__ uint32_t stream_head(uint32_t i) {
    return i - W0 < HK ? W0 / BPH : min(item_index(i) / BPH, (uint32_t)H);
}

__global__ void __launch_bounds__(NTHREADS, 1)
kv_decode_kernel(const int* __restrict__ qk, const int* __restrict__ qv,
                 const __nv_bfloat16* __restrict__ k_cos, const __nv_bfloat16* __restrict__ k_sin,
                 const __nv_bfloat16* __restrict__ ks, const __nv_bfloat16* __restrict__ kz,
                 const __nv_bfloat16* __restrict__ vs, const __nv_bfloat16* __restrict__ vz,
                 const __nv_bfloat16* __restrict__ q, const __nv_bfloat16* __restrict__ q_cos,
                 const __nv_bfloat16* __restrict__ q_sin, __nv_bfloat16* __restrict__ out, Scratch* __restrict__ sc,
                 unsigned int* __restrict__ ticket, const __grid_constant__ CUtensorMap vmap) {
    extern __shared__ __align__(128) unsigned char smem[];
    __shared__ __align__(8) uint64_t s_full[NST], s_empty[NST], s_qbar, s_wbar;
    __shared__ volatile int s_meta[NST];
    __shared__ volatile int s_flushed;
    __shared__ float4 s_hm[2][NHW];
    __shared__ uint32_t s_epoch;
    const int warp = __shfl_sync(0xffffffffu, threadIdx.x >> 5, 0), lane = threadIdx.x & 31;
    const uint32_t sbase = smem_u32(smem);
    const uint32_t nct = gridDim.x;
    constexpr int KU = KV_BYTES / 4096, NPRE = KLIM / (2 * KU);
    static_assert(NPRE >= 2 && W0 >= 2 * MAXCTA && MAXCTA <= BPH, "static items");
    uint64_t pol;
    asm volatile("createpolicy.fractional.L2::evict_first.b64 %0, 1.0;" : "=l"(pol));
    auto meta = [&](uint32_t idx, uint32_t nhead) {
        const uint32_t hb = (idx & (BPH - 1)) - held0(idx / BPH);
        return nhead | idx / BPH << 8 | (hb < HK ? (hb + 1) << 16 : 0);
    };
    auto issue = [&](int s, uint32_t idx) {
        const uint32_t blk = idx & (BPH - 1);
        const bool held = blk - held0(idx / BPH) < HK;
        const uint32_t bar = smem_u32(&s_full[s]), dst = sbase + s * SLOT;
        mbar_expect_tx(bar, held ? SLOT_TX - KV_BYTES : SLOT_TX);
        bulk_g2s_hint(dst + OFF_K, qk + (size_t)idx * (P * D), KV_BYTES, bar, pol);
        if (!held) bulk_g2s_hint(dst + OFF_V, qv + (size_t)idx * (P * D), KV_BYTES, bar, pol);
        bulk_g2s(dst + OFF_C, k_cos + blk * (P * D), CS_BYTES, bar);
        bulk_g2s(dst + OFF_S, k_sin + blk * (P * D), CS_BYTES, bar);
        bulk_g2s_hint(dst + OFF_KS, ks + idx * (P * 2), SC_BYTES, bar, pol);
        bulk_g2s_hint(dst + OFF_KZ, kz + idx * (P * 2), SC_BYTES, bar, pol);
        bulk_g2s_hint(dst + OFF_VS, vs + idx * (P * 2), SC_BYTES, bar, pol);
        bulk_g2s_hint(dst + OFF_VZ, vz + idx * (P * 2), SC_BYTES, bar, pol);
    };
    const bool leader = elect_one();
    const uint32_t tbase = (NPRE + 1 + X_STAT) * nct, twrap = NITEMS - tbase + nct - 1;
    uint32_t epoch, pend;
    if (leader) {
        if (warp < NST) {
            mbar_init(smem_u32(&s_full[warp]), 1);
            asm volatile("fence.mbarrier_init.release.cluster;" ::: "memory");
            if (warp == 0) {
                issue(0, blockIdx.x);
                if (X_EARLY) asm volatile("atom.relaxed.gpu.global.inc.u32 %0, [%1], %2;" : "=r"(pend) : "l"(ticket), "r"(twrap) : "memory");
                s_meta[0] = meta(blockIdx.x, (blockIdx.x + nct) / BPH);
            }
            if (warp == 1) asm volatile("ld.relaxed.gpu.global.u32 %0, [%1];" : "=r"(epoch) : "l"(&sc->epoch) : "memory");
            mbar_init(smem_u32(&s_empty[warp]), NCW);
        } else if (warp == NST) {
            mbar_init(smem_u32(&s_qbar), 1);
            asm volatile("fence.mbarrier_init.release.cluster;" ::: "memory");
            mbar_expect_tx(smem_u32(&s_qbar), Q_TX);
            bulk_g2s(sbase + OFF_Q, q, H * D * 2, smem_u32(&s_qbar));
            bulk_g2s(sbase + OFF_QC, q_cos, D * 2, smem_u32(&s_qbar));
            bulk_g2s(sbase + OFF_QS, q_sin, D * 2, smem_u32(&s_qbar));
            mbar_init(smem_u32(&s_wbar), NHW);
        }
    }
    __syncthreads();

    if (warp == 0) {
        if (leader) {
            STAMP(15);
            int s = 1, ph = 1, cnt = 1;
            int ls = 0, lph = 0, fl = blockIdx.x - held0(0) < HK ? KU : 2 * KU, ret = NST;
            uint32_t cost = fl;
            uint32_t cur = blockIdx.x + nct, nxt = cur + nct;
            const uint32_t c0 = clock32();
            uint32_t creq = c0, cgood = c0, vgood = 0;
#pragma unroll 1
            for (uint32_t live = opaque_zero();; live++) {
                do {
                    const uint32_t idx = item_index(cur);
                    const int c = (idx & (BPH - 1)) - held0(idx / BPH) < HK ? KU : 2 * KU;
                    fl += c;
                    while (fl > KLIM || (KLIM > NST * KU && cnt == ret)) {
                        mbar_wait(smem_u32(&s_full[ls]), lph);
                        fl -= (cost >> 4 * ls) & 15;
                        ret++;
                        if (++ls == NST) { ls = 0; lph ^= 1; }
                    }
                    if (cnt >= NST) mbar_wait(smem_u32(&s_empty[s]), ph);
                    cost = (cost & ~(15u << 4 * s)) | c << 4 * s;
                    s_meta[s] = meta(idx, stream_head(nxt));
                    issue(s, idx);
                    cnt++;
                    if (++s == NST) { s = 0; ph ^= 1; }
                    cur = nxt;
                    if (cur >= (uint32_t)NITEMS) break;
                    if (!X_EARLY && cnt == NPRE - 1)
                        asm volatile("atom.relaxed.gpu.global.inc.u32 %0, [%1], %2;" : "=r"(pend) : "l"(ticket), "r"(twrap) : "memory");
                    if (cnt < NPRE + X_STAT) { nxt += nct; continue; }
                    nxt = pend + tbase;
                    if (nxt < (uint32_t)NITEMS) {
                        asm volatile("atom.relaxed.gpu.global.inc.u32 %0, [%1], %2;" : "=r"(pend) : "l"(ticket), "r"(twrap) : "memory");
                        if (X_PACE) { cgood = creq; vgood = nxt; creq = clock32(); }
                        if ((idx & (X_SPF - 1)) < 4 && idx + X_SPA < NITEMS) {
                            const __nv_bfloat16* p = (idx & 2) ? ((idx & 1) ? vz : vs) : ((idx & 1) ? kz : ks);
                            asm volatile("cp.async.bulk.prefetch.L2.global.L2::cache_hint [%0], %1, %2;" ::"l"(p + ((idx & ~(X_SPF - 1)) + X_SPA) * (P * 2)), "n"(X_SPF * SC_BYTES), "l"(pol) : "memory");
                        }
                    }
                } while (live || cnt < NPRE);
                asm volatile("prefetch.tensormap [%0];" ::"l"(&vmap) : "memory");
                constexpr float STREAM = (float)NITEMS * (2 * KV_BYTES + 4 * SC_BYTES) + 2.f * S * D * 2 - (float)NOWN * NT * T_BYTES;
                const float per_byte = (float)(creq - c0) * (1.f / STREAM);
                const float ip = per_byte * (2 * KV_BYTES + 4 * SC_BYTES), tp = per_byte * (float)(min(nct, (uint32_t)NOWN) * T_BYTES);
                const uint32_t step = tp * (X_PB * 0.01f);
                uint32_t dl = creq + (uint32_t)(ip * nct * (2.f + X_PA * 0.01f) - (float)(cur - NITEMS) * (ip - (X_BURST ? 0.f : tp / nct)) * (X_PC * 0.01f));
                if (X_PACE == 2) dl = cgood + (uint32_t)(ip * (nct * (2.f + X_PA * 0.01f) + (float)(NITEMS - vgood)));
                if (X_BURST) dl += (blockIdx.x / OPH) * step * X_BURST / H;
#pragma unroll 1
                for (int o = blockIdx.x; o < NOWN; o += nct) {
#pragma unroll 1
                    for (int t = live ? 0 : NT - 1; t < NT; t++) {
                        if (live && X_PACE) {
                            for (int k = 0; (int)(clock32() - dl) < 0 && k < (1 << 20); k++);
                            if (X_BURST <= 1) { if (t < NT - 1 - X_FREE) dl += step; }
                            else if (t % X_BURST == X_BURST - 1 && t < NT - 1 - X_FREE) dl += min(X_BURST, NT - 1 - X_FREE - t + X_BURST - 1) * step;
                            mbar_wait(smem_u32(&s_empty[s]), ph);
                            cnt++;
                        } else if (live) {
                            fl += T_BYTES / 4096;
                            while ((fl > KLIMT && t < NT - X_FREE) || cnt == ret) {
                                mbar_wait(smem_u32(&s_full[ls]), lph);
                                fl -= (cost >> 4 * ls) & 15;
                        ret++;
                                if (++ls == NST) { ls = 0; lph ^= 1; }
                            }
                            mbar_wait(smem_u32(&s_empty[s]), ph);
                            cost = (cost & ~(15u << 4 * s)) | (T_BYTES / 4096) << 4 * s;
                            cnt++;
                        }
                        asm volatile("{ .reg .pred p; setp.ne.u32 p, %6, 0;\n"
                                     "@p mbarrier.arrive.expect_tx.shared.b64 _, [%2], %7;\n"
                                     "@p cp.async.bulk.tensor.2d.shared::cluster.global.mbarrier::complete_tx::bytes.L2::cache_hint "
                                     "[%0], [%1, {%3, %4}], [%2], %5; }" ::"r"(sbase + s * SLOT), "l"(&vmap), "r"(smem_u32(&s_full[s])),
                                     "r"((o % OPH) * QW), "r"((o / OPH) * S + held0(o / OPH) * P + t * TROWS), "l"(pol), "r"(live), "n"(T_BYTES) : "memory");
                        if (live && ++s == NST) { s = 0; ph ^= 1; }
                    }
                }
                if (live) break;
            }
        }
    } else if (warp <= NHW) {
        const int mw = warp - 1;
        if (warp == 1 && leader) { s_epoch = epoch; s_flushed = 0; }
        asm volatile("bar.sync 2, %0;" ::"n"(NTHREADS - 32) : "memory");
        const uint32_t tag = (s_epoch + 1) & 1;
        float* sw = reinterpret_cast<float*>(smem + OFF_W);
        const float* tr = reinterpret_cast<const float*>(smem + OFF_TR);
#pragma unroll 1
        for (int o = blockIdx.x; o < NOWN; o += nct) {
            const int h = o / OPH, col0 = (o % OPH) * QW;
            const uint2* pr = sc->row + (h * 2 + col0 / 64) * R + mw * HROWS;
            const int c0 = mw * RPI + lane / LR;
            const float4* pa = sc->acc + (size_t)(h * MAXCTA + c0) * 32 + col0 / 4 + (lane & (LR - 1));
            const float2* pm = sc->ml + h * MAXCTA + c0;
#pragma unroll 1
            for (uint32_t live = opaque_zero();; live++) {
                uint2 rw[NW];
                uint32_t bad = 0;
#pragma unroll
                for (int j = 0; j < NW; j++) {
                    rw[j] = make_uint2(0xff800000u, 0);
                    if (live && lane + 32 * j < NT * HROWS) bad |= 1u << j;
                }
                for (int k = 0; live && s_flushed <= (h == H - 1 ? min((int)(W0 / BPH) + 1, H - 2) : h); k++) { __nanosleep(X_SLEEP); if (k > (1 << 24)) __trap(); }
                for (int it = 0;; it++) {
#pragma unroll
                    for (int j = 0; j < NW; j++) {
                        const int i = lane + 32 * j;
                        asm volatile("{ .reg .pred p; .reg .b64 t; setp.ne.u32 p, %2, 0; mov.b64 t, {%0, %1};\n"
                                     "@p ld.relaxed.gpu.global.b64 t, [%3]; mov.b64 {%0, %1}, t; }"
                                     : "+r"(rw[j].x), "+r"(rw[j].y)
                                     : "r"(bad & (1u << j)), "l"(pr + i / HROWS * TROWS + i % HROWS) : "memory");
                    }
                    uint32_t nb = 0;
#pragma unroll
                    for (int j = NW - 1; j >= 0; j--) nb = nb * 2 + ((rw[j].x ^ tag) & 1);
                    bad &= nb;
                    if (!__any_sync(0xffffffffu, bad)) break;
                    __nanosleep(400);
                    if (it > (1 << 22)) __trap();
                }
                float Mr = NEG_INF, Lr = 0.f, Zr = 0.f;
#pragma unroll
                for (int j = 0; j < NW; j++) Mr = fmaxf(Mr, untag(rw[j].x));
#pragma unroll
                for (int x = 16; x > 0; x >>= 1) Mr = fmaxf(Mr, __shfl_xor_sync(0xffffffffu, Mr, x));
#pragma unroll
                for (int j = 0; j < NW; j++) {
                    const int i = lane + 32 * j;
                    const float p = exp_diff(untag(rw[j].x), Mr), w = p * bf_hi(rw[j].y);
                    Lr += p;
                    Zr = fmaf(w, bf_lo(rw[j].y), Zr);
                    if (i < NT * HROWS) sw[i / HROWS * TROWS + mw * HROWS + i % HROWS] = w;
                }
                __syncwarp();
                if (lane == 0 && live) mbar_arrive(smem_u32(&s_wbar));
#pragma unroll
                for (int x = 16; x > 0; x >>= 1) { Lr += __shfl_xor_sync(0xffffffffu, Lr, x); Zr += __shfl_xor_sync(0xffffffffu, Zr, x); }
                if (threadIdx.x == 32) STAMP(8);
                uint4 a[NJ]; uint2 ml[NJ];
#pragma unroll
                for (int j = 0; j < NJ; j++) {
                    a[j] = make_uint4(0, 0, 0, 0); ml[j] = make_uint2(0xff800000u, 0);
                    if (live && c0 + NHW * RPI * j < nct) bad |= 1u << j;
                }
                for (int k = 0; live && s_flushed <= min(h + X_LAG, H - 1); k++) { __nanosleep(X_SLEEP); if (k > (1 << 24)) __trap(); }
                if (threadIdx.x == 32) STAMP(9);
                for (int it = 0;; it++) {
#pragma unroll
                    for (int j = 0; j < NJ; j++) {
                        asm volatile("{ .reg .pred p; setp.ne.u32 p, %6, 0;\n"
                                     "@p ld.relaxed.gpu.global.v4.b32 {%0,%1,%2,%3}, [%7];\n"
                                     "@p ld.relaxed.gpu.global.v2.b32 {%4,%5}, [%8]; }"
                                     : "+r"(a[j].x), "+r"(a[j].y), "+r"(a[j].z), "+r"(a[j].w), "+r"(ml[j].x), "+r"(ml[j].y)
                                     : "r"(bad & (1u << j)), "l"(pa + NHW * RPI * 32 * j), "l"(pm + NHW * RPI * j) : "memory");
                    }
                    uint32_t nb = 0;
#pragma unroll
                    for (int j = NJ - 1; j >= 0; j--) {
                        uint32_t x;
                        asm volatile("{ .reg .b32 u, v;\n"
                            "lop3.b32 u, %1, %2, %7, 0x7e;\n lop3.b32 v, %3, %4, %7, 0x7e;\n lop3.b32 %0, %5, %6, %7, 0x7e;\n"
                            "lop3.b32 %0, %0, u, v, 0xfe; }"
                            : "=r"(x) : "r"(a[j].x), "r"(a[j].y), "r"(a[j].z), "r"(a[j].w), "r"(ml[j].x), "r"(ml[j].y), "r"(tag));
                        nb = nb * 2 + (x & 1);
                    }
                    bad &= nb;
                    if (!__any_sync(0xffffffffu, bad)) break;
                    if (X_BACKOFF) __nanosleep(X_BACKOFF);
                    if (it > (1 << 22)) __trap();
                }
                if (lane == 0) STAMP(10 + mw);
                float M = Mr;
#pragma unroll
                for (int j = 0; j < NJ; j++) M = fmaxf(M, untag(ml[j].x));
#pragma unroll
                for (int x = 16; x >= LR; x >>= 1) M = fmaxf(M, __shfl_xor_sync(0xffffffffu, M, x));
                const float fr = exp_diff(Mr, M);
                float o0 = 0.f, o1 = 0.f, o2 = 0.f, o3 = 0.f, L = 0.f;
#pragma unroll
                for (int j = 0; j < NJ; j++) {
                    const float e = exp_diff(untag(ml[j].x), M);
                    o0 = fmaf(e, untag(a[j].x), o0); o1 = fmaf(e, untag(a[j].y), o1);
                    o2 = fmaf(e, untag(a[j].z), o2); o3 = fmaf(e, untag(a[j].w), o3);
                    L = fmaf(e, untag(ml[j].y), L);
                }
                float* hb = reinterpret_cast<float*>(smem + OFF_HB) + live * NHW * QW;
                reduce_groups(hb + mw * QW, o0, o1, o2, o3, lane);
#pragma unroll
                for (int x = 16; x >= LR; x >>= 1) L += __shfl_xor_sync(0xffffffffu, L, x);
                if (lane == 0) s_hm[live][mw] = make_float4(M, fmaf(fr, Lr, L), fr, fr * Zr);
                asm volatile("bar.sync 3, %0;" ::"n"(NHW * 32) : "memory");
                float MM = NEG_INF, LL = 0.f, base = 0.f, g[NHW];
                const int col = (mw * 32 + lane) & (QW - 1);
#pragma unroll
                for (int w = 0; w < NHW; w++) MM = fmaxf(MM, s_hm[live][w].x);
#pragma unroll
                for (int w = 0; w < NHW; w++) {
                    const float4 x = s_hm[live][w];
                    const float e = exp_diff(x.x, MM);
                    LL = fmaf(e, x.y, LL);
                    base = fmaf(e, hb[w * QW + col] - x.w, base);
                    g[w] = e * x.z;
                }
                const float inv = __frcp_rn(LL);
                base *= inv;
#pragma unroll
                for (int w = 0; w < NHW; w++) g[w] *= inv;
                if (threadIdx.x == 32 && live) STAMP(5);
                asm volatile("{ .reg .pred p; setp.ne.u32 p, %0, 0; @p bar.sync 4, %1; }" ::"r"(live), "n"((NHW + NCW) * 32) : "memory");
#pragma unroll
                for (int w = 0; w < NHW; w++) {
                    float y = tr[w * QW + col];
                    if (NQ == 4) y = (y + tr[(NHW + w) * QW + col]) + (tr[(2 * NHW + w) * QW + col] + tr[(3 * NHW + w) * QW + col]);
                    else y += tr[(NHW + w) * QW + col];
                    g[w] *= y;
                }
                float y = base;
#pragma unroll
                for (int w = 0; w < NHW; w += 2) y += g[w] + g[w + 1];
                if (live && mw < QW / 32) out[h * D + col0 + col] = __float2bfloat16_rn(y);
                if (live) break;
            }
            if (o == NOWN - 1 && threadIdx.x == 32) sc->epoch = s_epoch + 1;
        }
        if (threadIdx.x == 32) STAMP(6);
    } else {
        const int cw = warp - 1 - NHW;
        const int hw = lane >> 4, li = lane & 15;
        int s = 0, ph = 0;
#pragma unroll 1
        for (uint32_t live = opaque_zero();; live++) {
        if (live) {
        asm volatile("bar.sync 2, %0;" ::"n"(NTHREADS - 32) : "memory");
        const uint32_t tag = (s_epoch + 1) & 1;
        mbar_wait(smem_u32(&s_qbar), 0);
        if (threadIdx.x == NTHREADS - 32) STAMP(1);
        int cur = stream_head(blockIdx.x), nflush = 0, qh = -1;
        if (cw == 0) for (int e = 0; e < cur; e++) publish(sc, e, lane, make_float4(0, 0, 0, 0), NEG_INF, 0.f, tag);
        float4 qlo, qhi;
        while (true) {
            float m = NEG_INF, lsum = 0.f, zsum = 0.f;
            float acc0 = 0.f, acc1 = 0.f, acc2 = 0.f, acc3 = 0.f;
            int nh;
            do {
                mbar_wait(smem_u32(&s_full[s]), ph);
                const int meta = s_meta[s];
                nh = meta & 255;
                if (NG > 1 && (s & (NG - 1)) != cw / GW) {
                    __syncwarp();
                    if (lane == 0) mbar_arrive(smem_u32(&s_empty[s]));
                    if (++s == NST) { s = 0; ph ^= 1; }
                    continue;
                }
                if (((meta >> 8) & 255) != qh) {
                    qh = (meta >> 8) & 255;
                    const uint2 l = lds64(sbase + OFF_Q + qh * 256 + li * 8), h = lds64(sbase + OFF_Q + qh * 256 + 128 + li * 8);
                    const uint2 cl = lds64(sbase + OFF_QC + li * 8), ch = lds64(sbase + OFF_QC + 128 + li * 8);
                    const uint2 sl = lds64(sbase + OFF_QS + li * 8), sh = lds64(sbase + OFF_QS + 128 + li * 8);
                    const uint32_t rl0 = bf2_sub(bf2_mul(l.x, cl.x), bf2_mul(h.x, sl.x));
                    const uint32_t rl1 = bf2_sub(bf2_mul(l.y, cl.y), bf2_mul(h.y, sl.y));
                    const uint32_t rh0 = bf2_add(bf2_mul(h.x, ch.x), bf2_mul(l.x, sh.x));
                    const uint32_t rh1 = bf2_add(bf2_mul(h.y, ch.y), bf2_mul(l.y, sh.y));
                    qlo = make_float4(bf_lo(rl0), bf_hi(rl0), bf_lo(rl1), bf_hi(rl1));
                    qhi = make_float4(bf_lo(rh0), bf_hi(rh0), bf_lo(rh1), bf_hi(rh1));
                }
                const uint32_t slot = sbase + s * SLOT;
                const int row0 = (cw & (GW - 1)) * RPW;
                float dot[RPW / 2];
#pragma unroll
                for (int it = 0; it < RPW / 2; it++) {
                    const int row = row0 + (RPW / 2) * hw + it;
                    const int4 a = lds128(slot + OFF_K + row * 512 + li * 16);
                    const int4 b = lds128(slot + OFF_K + row * 512 + 256 + li * 16);
                    const uint2 cl = lds64(slot + OFF_C + row * 256 + li * 8);
                    const uint2 ch = lds64(slot + OFF_C + row * 256 + 128 + li * 8);
                    const uint2 sl = lds64(slot + OFF_S + row * 256 + li * 8);
                    const uint2 sh = lds64(slot + OFF_S + row * 256 + 128 + li * 8);
                    const uint32_t sc = lds32(slot + OFF_KS + row * 4);
                    const uint32_t zc = lds32(slot + OFF_KZ + row * 4);
                    const uint32_t s0 = __byte_perm(sc, 0, 0x1010), s1 = __byte_perm(sc, 0, 0x3232);
                    const uint32_t z0 = __byte_perm(zc, 0, 0x1010), z1 = __byte_perm(zc, 0, 0x3232);
                    const uint32_t l0 = bf2_mul(bf2_sub(bf2_pack((float)a.x, (float)a.y), z0), s0);
                    const uint32_t l1 = bf2_mul(bf2_sub(bf2_pack((float)a.z, (float)a.w), z0), s0);
                    const uint32_t h0 = bf2_mul(bf2_sub(bf2_pack((float)b.x, (float)b.y), z1), s1);
                    const uint32_t h1 = bf2_mul(bf2_sub(bf2_pack((float)b.z, (float)b.w), z1), s1);
                    const uint32_t rl0 = bf2_sub(bf2_mul(l0, cl.x), bf2_mul(h0, sl.x));
                    const uint32_t rl1 = bf2_sub(bf2_mul(l1, cl.y), bf2_mul(h1, sl.y));
                    const uint32_t rh0 = bf2_add(bf2_mul(h0, ch.x), bf2_mul(l0, sh.x));
                    const uint32_t rh1 = bf2_add(bf2_mul(h1, ch.y), bf2_mul(l1, sh.y));
                    float d0 = qlo.x * bf_lo(rl0), d1 = qhi.x * bf_lo(rh0);
                    float d2 = qlo.z * bf_lo(rl1), d3 = qhi.z * bf_lo(rh1);
                    d0 = fmaf(qlo.y, bf_hi(rl0), d0); d1 = fmaf(qhi.y, bf_hi(rh0), d1);
                    d2 = fmaf(qlo.w, bf_hi(rl1), d2); d3 = fmaf(qhi.w, bf_hi(rh1), d3);
                    dot[it] = (d0 + d1) + (d2 + d3);
                }
                int4 v[RPW];
#pragma unroll
                for (int r = 0; r < RPW; r++) v[r] = lds128(slot + OFF_V + (row0 + r) * 512 + lane * 16);
                constexpr int LPR = 32 / RPW;
                const int myrow = row0 + lane / LPR;
                const uint32_t vsb = lds16(slot + OFF_VS + myrow * 4 + (lane & 1) * 2);
                const uint32_t vzb = lds16(slot + OFF_VZ + myrow * 4 + (lane & 1) * 2);
                const float vsc = __uint_as_float(vsb << 16), vzc = __uint_as_float(vzb << 16);
                __syncwarp();
                if (lane == 0) mbar_arrive(smem_u32(&s_empty[s]));
                if (++s == NST) { s = 0; ph ^= 1; }
                float t;
                if (RPW == 4) {
                    const bool up = lane & 8;
                    t = (up ? dot[RPW / 2 - 1] : dot[0]) + __shfl_xor_sync(0xffffffffu, up ? dot[0] : dot[RPW / 2 - 1], 8);
                } else {
                    t = dot[0] + __shfl_xor_sync(0xffffffffu, dot[0], 8);
                }
                t += __shfl_xor_sync(0xffffffffu, t, 4);
                t += __shfl_xor_sync(0xffffffffu, t, 2);
                t += __shfl_xor_sync(0xffffffffu, t, 1);
                const float lg = bf_round(bf_round(t) * 0.08838834764831845f);
                if (meta >> 16) {
                    if ((lane & (LPR - 1)) < 2)
                        asm volatile("{ .reg .b64 t; mov.b64 t, {%1, %2}; st.relaxed.gpu.global.b64 [%0], t; }"
                                     ::"l"(sc->row + (qh * 2 + (lane & 1)) * R + ((meta >> 16) - 1) * P + myrow),
                                     "r"(__float_as_uint(lg) | tag), "r"(vsb << 16 | vzb) : "memory");
                    continue;
                }
                float mx = fmaxf(lg, __shfl_xor_sync(0xffffffffu, lg, 16));
                if (RPW == 4) mx = fmaxf(mx, __shfl_xor_sync(0xffffffffu, mx, 8));
                const float mn = fmaxf(m, mx);
                const float alpha = exp_diff(m, mn);
                const float p = exp_diff(lg, mn);
                m = mn;
                const float c = p * vsc;
                lsum = fmaf(lsum, alpha, p);
                zsum = fmaf(zsum, alpha, c * vzc);
                acc0 *= alpha; acc1 *= alpha; acc2 *= alpha; acc3 *= alpha;
#pragma unroll
                for (int r = 0; r < RPW; r++) {
                    const float cr = __shfl_sync(0xffffffffu, c, LPR * r + hw);
                    acc0 = fmaf(cr, (float)v[r].x, acc0);
                    acc1 = fmaf(cr, (float)v[r].y, acc1);
                    acc2 = fmaf(cr, (float)v[r].z, acc2);
                    acc3 = fmaf(cr, (float)v[r].w, acc3);
                }
            } while (nh == cur);

            float* red = reinterpret_cast<float*>(smem + OFF_RED) + (nflush & 1) * NCW * RED_STRIDE;
            float l = lsum + __shfl_xor_sync(0xffffffffu, lsum, 16);
            float z = zsum + __shfl_xor_sync(0xffffffffu, zsum, 16);
            if (RPW == 4) { l += __shfl_xor_sync(0xffffffffu, l, 8); z += __shfl_xor_sync(0xffffffffu, z, 8); }
            z = __shfl_sync(0xffffffffu, z, hw);
            *reinterpret_cast<float4*>(red + cw * RED_STRIDE + 4 * lane) = make_float4(acc0 - z, acc1 - z, acc2 - z, acc3 - z);
            if (lane == 0) *reinterpret_cast<float2*>(red + cw * RED_STRIDE + D) = make_float2(m, l);
            asm volatile("bar.sync 1, %0;" ::"n"(NCW * 32) : "memory");
            if (cw == (nflush & (NCW - 1))) {
                float2 ml[NCW]; float M = NEG_INF;
#pragma unroll
                for (int w = 0; w < NCW; w++) { ml[w] = *reinterpret_cast<const float2*>(red + w * RED_STRIDE + D); M = fmaxf(M, ml[w].x); }
                float4 a = make_float4(0, 0, 0, 0); float L = 0.f;
#pragma unroll
                for (int w = 0; w < NCW; w++) {
                    const float e = exp_diff(ml[w].x, M);
                    const float4 t = *reinterpret_cast<const float4*>(red + w * RED_STRIDE + 4 * lane);
                    a.x += e * t.x; a.y += e * t.y; a.z += e * t.z; a.w += e * t.w;
                    L += e * ml[w].y;
                }
                publish(sc, cur, lane, a, M, L, tag);
                for (int e = cur + 1; e < nh; e++) publish(sc, e, lane, make_float4(0, 0, 0, 0), NEG_INF, 0.f, tag);
                if (lane == 0) s_flushed = nh;
            }
            nflush++;
            if (nh >= H) break;
            cur = nh;
        }

        }
        const uint32_t wofs = ((cw & (NHW - 1)) * RPI + lane / LR) * KPL;
        uint32_t wph = 0;
#pragma unroll 1
        for (int o = blockIdx.x; o < NOWN; o += nct) {
            float o0 = 0.f, o1 = 0.f, o2 = 0.f, o3 = 0.f;
            if (live) mbar_wait(smem_u32(&s_wbar), wph);
            wph ^= 1;
#pragma unroll 1
            for (int t = live ? (cw / NHW - s) & (NQ - 1) : NT - 1; t < NT; t += NQ) {
                float c[KPL];
#pragma unroll
                for (int k = 0; k < KPL; k++) c[k] = reinterpret_cast<const float*>(smem + OFF_W)[t * TROWS + wofs + k];
                const int ts = (s + t) % NST;
                if (live) mbar_wait(smem_u32(&s_full[ts]), ph ^ ((s + t) / NST & 1));
                if (lane == 0 && (cw & (NHW - 1)) == 0 && t == NT - 1 && live) STAMP(7);
                int4 v[KPL];
#pragma unroll
                for (int k = 0; k < KPL; k++) v[k] = lds128(sbase + ts * SLOT + (wofs + k) * (QW * 4) + (lane & (LR - 1)) * 16);
                __syncwarp();
                if (lane == 0 && live)
                    asm volatile("mbarrier.arrive.shared.b64 _, [%0], %1;" ::"r"(smem_u32(&s_empty[ts])), "n"(NQ) : "memory");
#pragma unroll
                for (int k = 0; k < KPL; k++) {
                    o0 = fmaf(c[k], (float)v[k].x, o0); o1 = fmaf(c[k], (float)v[k].y, o1);
                    o2 = fmaf(c[k], (float)v[k].z, o2); o3 = fmaf(c[k], (float)v[k].w, o3);
                }
            }
            if (live) { ph ^= (s + NT) / NST & 1; s = (s + NT) % NST; }
            reduce_groups(reinterpret_cast<float*>(smem + OFF_TR) + cw * QW, o0, o1, o2, o3, lane);
            asm volatile("{ .reg .pred p; setp.ne.u32 p, %0, 0; @p bar.arrive 4, %1; }" ::"r"(live), "n"((NHW + NCW) * 32) : "memory");
        }
        if (live) break;
        }
    }
}

}
extern "C" void kernel_launch(void* const* d_in, const int* in_sizes, int n_in, void* d_out, int out_size) {
    typedef CUresult (*EncodeFn)(CUtensorMap*, CUtensorMapDataType, cuuint32_t, void*, const cuuint64_t*, const cuuint64_t*,
                                 const cuuint32_t*, const cuuint32_t*, CUtensorMapInterleave, CUtensorMapSwizzle,
                                 CUtensorMapL2promotion, CUtensorMapFloatOOBfill);
    static int nsm = 0;
    static EncodeFn encode = nullptr;
    static Scratch* sc = nullptr;
    if (nsm == 0) {
        int dev = 0;
        cudaGetDevice(&dev);
        cudaDeviceGetAttribute(&nsm, cudaDevAttrMultiProcessorCount, dev);
        if (nsm > MAXCTA) nsm = MAXCTA;
        cudaFuncSetAttribute(kv_decode_kernel, cudaFuncAttributeMaxDynamicSharedMemorySize, SMEM_BYTES);
        cudaGetSymbolAddress((void**)&sc, g_scratch);
        cudaDriverEntryPointQueryResult qr;
        cudaGetDriverEntryPoint("cuTensorMapEncodeTiled", (void**)&encode, cudaEnableDefault, &qr);
    }
    CUtensorMap vmap;
    const cuuint64_t gdim[2] = {(cuuint64_t)D, (cuuint64_t)H * S};
    const cuuint64_t gstr[1] = {(cuuint64_t)D * 4};
    const cuuint32_t box[2] = {(cuuint32_t)QW, (cuuint32_t)TROWS};
    const cuuint32_t estr[2] = {1, 1};
    encode(&vmap, CU_TENSOR_MAP_DATA_TYPE_INT32, 2, d_in[4], gdim, gstr, box, estr, CU_TENSOR_MAP_INTERLEAVE_NONE,
           CU_TENSOR_MAP_SWIZZLE_NONE, X_PROMO, CU_TENSOR_MAP_FLOAT_OOB_FILL_NONE);
    kv_decode_kernel<<<nsm, NTHREADS, SMEM_BYTES>>>(
        (const int*)d_in[1], (const int*)d_in[4], (const __nv_bfloat16*)d_in[9], (const __nv_bfloat16*)d_in[10],
        (const __nv_bfloat16*)d_in[2], (const __nv_bfloat16*)d_in[3], (const __nv_bfloat16*)d_in[5],
        (const __nv_bfloat16*)d_in[6], (const __nv_bfloat16*)d_in[0], (const __nv_bfloat16*)d_in[7],
        (const __nv_bfloat16*)d_in[8], (__nv_bfloat16*)d_out, sc,
        &sc->ticket, vmap);
}
```

```cpp
#include <cuda_runtime.h>
#include <cuda.h>
#include <cuda_bf16.h>
#include <stdint.h>
#include <stddef.h>

#define KNST 8
#define KNT 16
#define KLIM 12
#define X_FREE 3
#define X_PA 90
#define X_B0 124
#define X_B1 -4
#define X_W0 8448
#define X_BACKOFF 100
#define X_SLEEP 64
#define X_SPF 64
#define X_SPA 1024
#define X_FIN 1
#define NCW 8
#define NHW 4
#define NTHREADS ((1 + NHW + NCW) * 32)

namespace {

constexpr int H = 32, S = 8192, D = 128;
constexpr int P = 16, NST = KNST;
constexpr int BPH = S / P;
constexpr int NITEMS = BPH * H;
constexpr int RPW = P / NCW;
constexpr int MAXCTA = 144;
static_assert(RPW == 2, "rows per warp");

constexpr int QW = 32, OPH = D / QW, NOWN = H * OPH;
constexpr int LR = QW / 4, RPI = 32 / LR;
constexpr uint32_t T_BYTES = 8192;
constexpr int NT = KNT, TROWS = T_BYTES / (QW * 4), R = NT * TROWS;
constexpr int KPL = T_BYTES / (NHW * 512);
constexpr int NQ = NCW / NHW;
constexpr uint32_t HK = R / P;
constexpr int HROWS = TROWS / NHW;
constexpr int NW = (NT * HROWS + 31) / 32;
constexpr int NJ = (MAXCTA + NHW * RPI - 1) / (NHW * RPI);
static_assert(NT % 2 == 0 && NQ == 2 && R % P == 0 && R < S && NST <= 8, "held-back rows");

constexpr uint32_t KV_BYTES = P * D * 4;
constexpr uint32_t CS_BYTES = P * D * 2;
constexpr uint32_t SC_BYTES = P * 4;
constexpr uint32_t OFF_K = 0, OFF_V = KV_BYTES, OFF_C = 2 * KV_BYTES, OFF_S = OFF_C + CS_BYTES;
constexpr uint32_t OFF_KS = OFF_S + CS_BYTES, OFF_KZ = OFF_KS + SC_BYTES, OFF_VS = OFF_KZ + SC_BYTES,
                   OFF_VZ = OFF_VS + SC_BYTES;
constexpr uint32_t SLOT_TX = OFF_VZ + SC_BYTES;
constexpr uint32_t SLOT = (SLOT_TX + 127) / 128 * 128;
constexpr uint32_t OFF_Q = NST * SLOT;
constexpr uint32_t OFF_QC = OFF_Q + H * D * 2, OFF_QS = OFF_QC + D * 2;
constexpr uint32_t Q_TX = H * D * 2 + 2 * D * 2;
constexpr uint32_t OFF_RED = OFF_Q + Q_TX;
constexpr uint32_t RED_STRIDE = D + 4;
constexpr uint32_t OFF_W = OFF_RED + 2 * NCW * RED_STRIDE * 4;
constexpr uint32_t OFF_TR = OFF_W + R * 4;
constexpr uint32_t OFF_HB = OFF_TR + NCW * QW * 4;
constexpr uint32_t SMEM_BYTES = OFF_HB + 2 * NHW * QW * 4;

struct Scratch {
    float4 acc[H * MAXCTA * 32];
    float2 ml[H * MAXCTA];
    uint2 row[H * 2 * R];
    alignas(128) unsigned int ticket[64];
};
__device__ Scratch g_scratch;
#define STAMP(i)

__device__ __forceinline__ uint32_t smem_u32(const void* p) { return (uint32_t)__cvta_generic_to_shared(p); }
__device__ __forceinline__ bool elect_one() {
    uint32_t p;
    asm volatile("{ .reg .pred p; elect.sync _|p, 0xffffffff; selp.u32 %0, 1, 0, p; }" : "=r"(p));
    return p;
}
__device__ __forceinline__ uint32_t opaque_zero() {
    uint32_t z;
    asm volatile("mov.u32 %0, 0;" : "=r"(z));
    return z;
}
__device__ __forceinline__ uint32_t clock32() {
    uint32_t c;
    asm volatile("mov.u32 %0, %clock;" : "=r"(c));
    return c;
}
__device__ __forceinline__ void mbar_init(uint32_t bar, uint32_t cnt) {
    asm volatile("mbarrier.init.shared.b64 [%0], %1;" ::"r"(bar), "r"(cnt) : "memory");
}
__device__ __forceinline__ void mbar_expect_tx(uint32_t bar, uint32_t bytes) {
    asm volatile("mbarrier.arrive.expect_tx.shared.b64 _, [%0], %1;" ::"r"(bar), "r"(bytes) : "memory");
}
__device__ __forceinline__ void mbar_arrive(uint32_t bar) {
    asm volatile("mbarrier.arrive.shared.b64 _, [%0];" ::"r"(bar) : "memory");
}
__device__ __forceinline__ void mbar_wait(uint32_t bar, uint32_t parity) {
    uint32_t done;
    int it = 0;
    do {
        asm volatile("{ .reg .pred p; mbarrier.try_wait.parity.shared.b64 p, [%1], %2; selp.u32 %0, 1, 0, p; }"
                     : "=r"(done) : "r"(bar), "r"(parity) : "memory");
        if (++it > (1 << 24)) __trap();
    } while (!done);
}
__device__ __forceinline__ void bulk_g2s(uint32_t dst, const void* src, uint32_t bytes, uint32_t bar) {
    asm volatile("cp.async.bulk.shared::cluster.global.mbarrier::complete_tx::bytes [%0], [%1], %2, [%3];"
                 ::"r"(dst), "l"(src), "r"(bytes), "r"(bar) : "memory");
}
__device__ __forceinline__ void bulk_g2s_hint(uint32_t dst, const void* src, uint32_t bytes, uint32_t bar, uint64_t pol) {
    asm volatile("cp.async.bulk.shared::cluster.global.mbarrier::complete_tx::bytes.L2::cache_hint [%0], [%1], %2, [%3], %4;"
                 ::"r"(dst), "l"(src), "r"(bytes), "r"(bar), "l"(pol) : "memory");
}
__device__ __forceinline__ int4 lds128(uint32_t a) {
    int4 v;
    asm volatile("ld.shared.v4.s32 {%0,%1,%2,%3}, [%4];" : "=r"(v.x), "=r"(v.y), "=r"(v.z), "=r"(v.w) : "r"(a));
    return v;
}
__device__ __forceinline__ uint2 lds64(uint32_t a) {
    uint2 v;
    asm volatile("ld.shared.v2.u32 {%0,%1}, [%2];" : "=r"(v.x), "=r"(v.y) : "r"(a));
    return v;
}
__device__ __forceinline__ uint32_t lds32(uint32_t a) {
    uint32_t v;
    asm volatile("ld.shared.u32 %0, [%1];" : "=r"(v) : "r"(a));
    return v;
}
__device__ __forceinline__ uint32_t lds16(uint32_t a) {
    uint16_t v;
    asm volatile("ld.shared.u16 %0, [%1];" : "=h"(v) : "r"(a));
    return v;
}
__device__ __forceinline__ uint32_t bf2_mul(uint32_t a, uint32_t b) {
    uint32_t d; asm("mul.rn.bf16x2 %0, %1, %2;" : "=r"(d) : "r"(a), "r"(b)); return d;
}
__device__ __forceinline__ uint32_t bf2_add(uint32_t a, uint32_t b) {
    uint32_t d; asm("add.rn.bf16x2 %0, %1, %2;" : "=r"(d) : "r"(a), "r"(b)); return d;
}
__device__ __forceinline__ uint32_t bf2_sub(uint32_t a, uint32_t b) {
    uint32_t d; asm("sub.rn.bf16x2 %0, %1, %2;" : "=r"(d) : "r"(a), "r"(b)); return d;
}
__device__ __forceinline__ uint32_t bf2_pack(float lo, float hi) {
    uint32_t d; asm("cvt.rn.bf16x2.f32 %0, %1, %2;" : "=r"(d) : "f"(hi), "f"(lo)); return d;
}
__device__ __forceinline__ float bf_lo(uint32_t v) { return __uint_as_float(v << 16); }
__device__ __forceinline__ float bf_hi(uint32_t v) { return __uint_as_float(v & 0xffff0000u); }
__device__ __forceinline__ float bf_round(float x) { return __bfloat162float(__float2bfloat16_rn(x)); }
__device__ __forceinline__ float ex2(float x) { float y; asm("ex2.approx.ftz.f32 %0, %1;" : "=f"(y) : "f"(x)); return y; }

constexpr float LOG2E = 1.4426950408889634f;
constexpr float NEG_INF = -__builtin_huge_valf();

__device__ __forceinline__ float exp_diff(float a, float b) {
    return (a == NEG_INF) ? 0.f : ex2((a - b) * LOG2E);
}

__device__ __forceinline__ uint32_t tagw(float x, uint32_t tag) { return (__float_as_uint(x) & ~1u) | tag; }
__device__ __forceinline__ float untag(uint32_t x) { return __uint_as_float(x & ~1u); }
__device__ __forceinline__ void publish(Scratch* sc, int h, int lane, float4 a, float M, float L, uint32_t tag) {
    float4* pa = sc->acc + (size_t)(h * MAXCTA + blockIdx.x) * 32 + lane;
    asm volatile("st.relaxed.gpu.global.v4.b32 [%0], {%1,%2,%3,%4};" ::"l"(pa), "r"(tagw(a.x, tag)), "r"(tagw(a.y, tag)),
                 "r"(tagw(a.z, tag)), "r"(tagw(a.w, tag)) : "memory");
    if (lane == 0)
        asm volatile("st.relaxed.gpu.global.v2.b32 [%0], {%1,%2};" ::"l"(sc->ml + h * MAXCTA + blockIdx.x),
                     "r"(tagw(M, tag)), "r"(tagw(L, tag)) : "memory");
}

__device__ __forceinline__ void reduce_groups(float* dst, float o0, float o1, float o2, float o3, int lane) {
    const bool hi = lane & 16;
    const float r0 = (hi ? o2 : o0) + __shfl_xor_sync(0xffffffffu, hi ? o0 : o2, 16);
    const float r1 = (hi ? o3 : o1) + __shfl_xor_sync(0xffffffffu, hi ? o1 : o3, 16);
    dst += (lane & (LR - 1)) * 4 + hi * 2;
    if (RPI == 4) {
        const bool up = lane & 8;
        dst[up] = (up ? r1 : r0) + __shfl_xor_sync(0xffffffffu, up ? r0 : r1, 8);
    } else {
        *reinterpret_cast<float2*>(dst) = make_float2(r0, r1);
    }
}

__device__ __forceinline__ uint32_t held0(uint32_t h) { return X_B0 + (int)h * (X_B1); }
constexpr uint32_t W0 = X_W0, LAST0 = (H - 1) * BPH + X_B0 + (H - 1) * (X_B1);
__device__ __forceinline__ uint32_t item_index(uint32_t i) {
    return i - W0 < HK ? LAST0 + i - W0 : i - W0 < LAST0 + HK - W0 ? i - HK : i;
}
__device__ __forceinline__ uint32_t stream_head(uint32_t i) {
    return i - W0 < HK ? W0 / BPH : min(item_index(i) / BPH, (uint32_t)H);
}

__global__ void __launch_bounds__(NTHREADS, 1)
kv_decode_kernel(const int* __restrict__ qk, const int* __restrict__ qv,
                 const __nv_bfloat16* __restrict__ k_cos, const __nv_bfloat16* __restrict__ k_sin,
                 unsigned int* __restrict__ ticket, const uint32_t nct,
                 const __nv_bfloat16* __restrict__ ks, const __nv_bfloat16* __restrict__ kz,
                 const __nv_bfloat16* __restrict__ vs, const __nv_bfloat16* __restrict__ vz,
                 const __nv_bfloat16* __restrict__ q, const __nv_bfloat16* __restrict__ q_cos,
                 const __nv_bfloat16* __restrict__ q_sin, __nv_bfloat16* __restrict__ out, Scratch* __restrict__ sc,
                 const __grid_constant__ CUtensorMap vmap) {
    extern __shared__ __align__(128) unsigned char smem[];
    __shared__ __align__(8) uint64_t s_full[NST], s_empty[NST], s_qbar, s_wbar, s_tile[NT];
    __shared__ volatile int s_meta[NST];
    __shared__ volatile int s_tick;
    __shared__ volatile int s_flushed;
    __shared__ float4 s_hm[2][NHW];
    __shared__ uint32_t s_epoch;
    const uint32_t sbase = smem_u32(smem);
    uint64_t pol;
    asm("createpolicy.fractional.L2::evict_first.b64 %0, 1.0;" : "=l"(pol));
    const bool leader = elect_one();
    static_assert(2 * MAXCTA <= BPH, "first item");
    uint32_t c0;
    if (threadIdx.x < 32 && leader) {
        const uint32_t bar = smem_u32(&s_full[0]);
        mbar_init(bar, 1);
        asm volatile("fence.mbarrier_init.release.cluster;" ::: "memory");
        uint32_t ofs;
        asm volatile("mov.u32 %0, %ctaid.x;" : "=r"(ofs));
        const bool held = ofs - held0(0) < HK;
        ofs *= P * D;
        mbar_expect_tx(bar, (held ? KV_BYTES : 2 * KV_BYTES) + 2 * CS_BYTES);
        c0 = clock32();
        bulk_g2s_hint(sbase + OFF_K, qk + ofs, KV_BYTES, bar, pol);
        if (!held) bulk_g2s_hint(sbase + OFF_V, qv + ofs, KV_BYTES, bar, pol);
        bulk_g2s(sbase + OFF_C, k_cos + ofs, CS_BYTES, bar);
        bulk_g2s(sbase + OFF_S, k_sin + ofs, CS_BYTES, bar);
    }
    __syncwarp();
    constexpr int KU = KV_BYTES / 4096, NPRE = KLIM / (2 * KU);
    const uint32_t tbase = (NPRE + 1) * nct, twrap = NITEMS - tbase + nct - 1;
    uint32_t epoch, pend;
    asm volatile("{ .reg .pred p; setp.ne.u32 p, %4, 0;\n"
                 "@p atom.relaxed.gpu.global.inc.u32 %0, [%2], %3;\n"
                 "@p ld.relaxed.gpu.global.u32 %1, [%2 + 128]; }"
                 : "=r"(pend), "=r"(epoch) : "l"(ticket), "r"(twrap), "r"((uint32_t)(leader && threadIdx.x >> 5 == 1)) : "memory");
    const int warp = __shfl_sync(0xffffffffu, threadIdx.x >> 5, 0), lane = threadIdx.x & 31;
    static_assert(NPRE >= 2 && KLIM <= NST * KU && W0 >= 2 * MAXCTA && MAXCTA <= BPH, "static items");
    auto meta = [&](uint32_t idx, uint32_t nhead) {
        const uint32_t hb = (idx & (BPH - 1)) - held0(idx / BPH);
        return nhead | idx / BPH << 8 | (hb < HK ? (hb + 1) << 16 : 0);
    };
    auto issue = [&](int s, uint32_t idx) {
        const uint32_t blk = idx & (BPH - 1);
        const bool held = blk - held0(idx / BPH) < HK;
        const uint32_t bar = smem_u32(&s_full[s]), dst = sbase + s * SLOT;
        mbar_expect_tx(bar, held ? SLOT_TX - KV_BYTES : SLOT_TX);
        bulk_g2s_hint(dst + OFF_K, qk + (size_t)idx * (P * D), KV_BYTES, bar, pol);
        if (!held) bulk_g2s_hint(dst + OFF_V, qv + (size_t)idx * (P * D), KV_BYTES, bar, pol);
        bulk_g2s(dst + OFF_C, k_cos + blk * (P * D), CS_BYTES, bar);
        bulk_g2s(dst + OFF_S, k_sin + blk * (P * D), CS_BYTES, bar);
        bulk_g2s_hint(dst + OFF_KS, ks + idx * (P * 2), SC_BYTES, bar, pol);
        bulk_g2s_hint(dst + OFF_KZ, kz + idx * (P * 2), SC_BYTES, bar, pol);
        bulk_g2s_hint(dst + OFF_VS, vs + idx * (P * 2), SC_BYTES, bar, pol);
        bulk_g2s_hint(dst + OFF_VZ, vz + idx * (P * 2), SC_BYTES, bar, pol);
    };
    if (leader) {
        if (warp < NST) {
            if (warp == 0) {
                s_meta[0] = meta(blockIdx.x, 0);
                s_tick = -1;
            } else {
                mbar_init(smem_u32(&s_full[warp]), 1);
            }
            mbar_init(smem_u32(&s_empty[warp]), NCW);
            asm volatile("fence.mbarrier_init.release.cluster;" ::: "memory");
        } else if (warp == NST) {
            const uint32_t bar = smem_u32(&s_qbar);
            mbar_init(bar, 1);
            asm volatile("fence.mbarrier_init.release.cluster;" ::: "memory");
            mbar_expect_tx(bar, Q_TX + 4 * SC_BYTES);
            bulk_g2s_hint(sbase + OFF_KS, ks + blockIdx.x * (P * 2), SC_BYTES, bar, pol);
            bulk_g2s_hint(sbase + OFF_KZ, kz + blockIdx.x * (P * 2), SC_BYTES, bar, pol);
            bulk_g2s_hint(sbase + OFF_VS, vs + blockIdx.x * (P * 2), SC_BYTES, bar, pol);
            bulk_g2s_hint(sbase + OFF_VZ, vz + blockIdx.x * (P * 2), SC_BYTES, bar, pol);
            bulk_g2s(sbase + OFF_Q, q, H * D * 2, bar);
            bulk_g2s(sbase + OFF_QC, q_cos, D * 2, bar);
            bulk_g2s(sbase + OFF_QS, q_sin, D * 2, bar);
            mbar_init(smem_u32(&s_wbar), NHW);
        } else if (warp == NST + 1) {
            for (int t = 0; t < NT; t++) mbar_init(smem_u32(&s_tile[t]), 1);
            asm volatile("fence.mbarrier_init.release.cluster;" ::: "memory");
        } else if (warp == NST + 2) {
            asm volatile("prefetch.tensormap [%0];" ::"l"(&vmap) : "memory");
        }
    }
    __syncthreads();

    if (warp == 0) {
        if (leader) {
            STAMP(15);
            unsigned int* const tk = ticket + (threadIdx.x >> 5);
            int s = 1, ph = 1, cnt = 1;
            int ls = 0, lph = 0, fl = blockIdx.x - held0(0) < HK ? KU : 2 * KU;
            uint32_t cost = fl;
            uint32_t cur = blockIdx.x + nct, nxt = cur + nct;
            uint32_t creq = c0, cgood = c0, vgood = 0;
#pragma unroll 1
            for (uint32_t live = opaque_zero();; live++) {
                do {
                    const uint32_t idx = item_index(cur);
                    const int c = (idx & (BPH - 1)) - held0(idx / BPH) < HK ? KU : 2 * KU;
                    fl += c;
                    while (fl > KLIM) {
                        mbar_wait(smem_u32(&s_full[ls]), lph);
                        fl -= (cost >> 4 * ls) & 15;
                        if (++ls == NST) { ls = 0; lph ^= 1; }
                    }
                    if (cnt >= NST) mbar_wait(smem_u32(&s_empty[s]), ph);
                    cost = (cost & ~(15u << 4 * s)) | c << 4 * s;
                    s_meta[s] = meta(idx, stream_head(nxt));
                    issue(s, idx);
                    cnt++;
                    if (++s == NST) { s = 0; ph ^= 1; }
                    cur = nxt;
                    if (cur >= (uint32_t)NITEMS) break;
                    if (cnt < NPRE) { nxt += nct; continue; }
                    if (!live) for (int k = 0; (int)(pend = s_tick) < 0; k++) if (k > (1 << 24)) __trap();
                    nxt = pend + tbase;
                    if (nxt < (uint32_t)NITEMS) {
                        asm volatile("atom.relaxed.gpu.global.inc.u32 %0, [%1], %2;" : "=r"(pend) : "l"(tk), "r"(twrap) : "memory");
                        cgood = creq; vgood = nxt; creq = clock32();
                        if ((idx & (X_SPF - 1)) < 4 && idx + X_SPA < NITEMS) {
                            const __nv_bfloat16* p = (idx & 2) ? ((idx & 1) ? vz : vs) : ((idx & 1) ? kz : ks);
                            asm volatile("cp.async.bulk.prefetch.L2.global.L2::cache_hint [%0], %1, %2;" ::"l"(p + ((idx & ~(X_SPF - 1)) + X_SPA) * (P * 2)), "n"(X_SPF * SC_BYTES), "l"(pol) : "memory");
                        }
                    }
                } while (live || cnt < NPRE);
                asm volatile("prefetch.tensormap [%0];" ::"l"(&vmap) : "memory");
                constexpr float STREAM = (float)NITEMS * (2 * KV_BYTES + 4 * SC_BYTES) + 2.f * S * D * 2 - (float)NOWN * NT * T_BYTES;
                const float per_byte = (float)(creq - c0) * (1.f / STREAM);
                const float ip = per_byte * (2 * KV_BYTES + 4 * SC_BYTES), tp = per_byte * (float)(min(nct, (uint32_t)NOWN) * T_BYTES);
                const uint32_t step = tp;
                uint32_t dl = cgood + (uint32_t)(ip * (nct * (2.f + X_PA * 0.01f) + (float)(NITEMS - vgood))) + (blockIdx.x / OPH) * step / H;
#pragma unroll 1
                for (int o = blockIdx.x; o < NOWN; o += nct) {
#pragma unroll 1
                    for (int t = live ? 0 : NT - 1; t < NT; t++) {
                        if (live) {
                            for (int k = 0; (int)(clock32() - dl) < 0 && k < (1 << 20); k++);
                            if (t < NT - 1 - X_FREE) dl += step;
                            if (!(t & 1)) mbar_wait(smem_u32(&s_empty[s]), ph);
                        }
                        asm volatile("{ .reg .pred p; setp.ne.u32 p, %6, 0;\n"
                                     "@p mbarrier.arrive.expect_tx.shared.b64 _, [%2], %7;\n"
                                     "@p cp.async.bulk.tensor.2d.shared::cluster.global.mbarrier::complete_tx::bytes.L2::cache_hint "
                                     "[%0], [%1, {%3, %4}], [%2], %5; }" ::"r"(sbase + s * SLOT + (t & 1) * T_BYTES), "l"(&vmap), "r"(smem_u32(&s_tile[t])),
                                     "r"((o % OPH) * QW), "r"((o / OPH) * S + held0(o / OPH) * P + t * TROWS), "l"(pol), "r"(live), "n"(T_BYTES) : "memory");
                        if (live && (t & 1) && ++s == NST) { s = 0; ph ^= 1; }
                    }
                }
                if (live) break;
            }
        }
    } else if (warp <= NHW) {
        const int mw = warp - 1;
        {
        if (warp == 1 && leader) { s_tick = pend; s_epoch = epoch; s_flushed = 0; }
        asm volatile("bar.sync 2, %0;" ::"n"(NTHREADS - 32) : "memory");
        }
        const uint32_t tag = (s_epoch + 1) & 1;
        float* sw = reinterpret_cast<float*>(smem + OFF_W);
#pragma unroll 1
        for (int o = blockIdx.x; o < NOWN; o += nct) {
            const int h = o / OPH, col0 = (o % OPH) * QW;
            const uint2* pr = sc->row + (h * 2 + col0 / 64) * R + mw * HROWS;
            const int c0 = mw * RPI + lane / LR;
            const float4* pa = sc->acc + (size_t)(h * MAXCTA + c0) * 32 + col0 / 4 + (lane & (LR - 1));
            const float2* pm = sc->ml + h * MAXCTA + c0;
#pragma unroll 1
            for (uint32_t live = opaque_zero();; live++) {
                uint2 rw[NW];
                uint32_t bad = 0;
#pragma unroll
                for (int j = 0; j < NW; j++) {
                    rw[j] = make_uint2(0xff800000u, 0);
                    if (live && lane + 32 * j < NT * HROWS) bad |= 1u << j;
                }
                for (int k = 0; live && s_flushed <= (h == H - 1 ? min((int)(W0 / BPH) + 1, H - 2) : h); k++) { __nanosleep(X_SLEEP); if (k > (1 << 24)) __trap(); }
                for (int it = 0;; it++) {
#pragma unroll
                    for (int j = 0; j < NW; j++) {
                        const int i = lane + 32 * j;
                        asm volatile("{ .reg .pred p; .reg .b64 t; setp.ne.u32 p, %2, 0; mov.b64 t, {%0, %1};\n"
                                     "@p ld.relaxed.gpu.global.b64 t, [%3]; mov.b64 {%0, %1}, t; }"
                                     : "+r"(rw[j].x), "+r"(rw[j].y)
                                     : "r"(bad & (1u << j)), "l"(pr + i / HROWS * TROWS + i % HROWS) : "memory");
                    }
                    uint32_t nb = 0;
#pragma unroll
                    for (int j = NW - 1; j >= 0; j--) nb = nb * 2 + ((rw[j].x ^ tag) & 1);
                    bad &= nb;
                    if (!__any_sync(0xffffffffu, bad)) break;
                    __nanosleep(400);
                    if (it > (1 << 22)) __trap();
                }
                float Mr = NEG_INF, Lr = 0.f, Zr = 0.f;
#pragma unroll
                for (int j = 0; j < NW; j++) Mr = fmaxf(Mr, untag(rw[j].x));
#pragma unroll
                for (int x = 16; x > 0; x >>= 1) Mr = fmaxf(Mr, __shfl_xor_sync(0xffffffffu, Mr, x));
#pragma unroll
                for (int j = 0; j < NW; j++) {
                    const int i = lane + 32 * j;
                    const float p = exp_diff(untag(rw[j].x), Mr), w = p * bf_hi(rw[j].y);
                    Lr += p;
                    Zr = fmaf(w, bf_lo(rw[j].y), Zr);
                    if (i < NT * HROWS) sw[i / HROWS * TROWS + mw * HROWS + i % HROWS] = w;
                }
                __syncwarp();
                if (lane == 0 && live) mbar_arrive(smem_u32(&s_wbar));
#pragma unroll
                for (int x = 16; x > 0; x >>= 1) { Lr += __shfl_xor_sync(0xffffffffu, Lr, x); Zr += __shfl_xor_sync(0xffffffffu, Zr, x); }
                if (threadIdx.x == 32) STAMP(8);
                uint4 a[NJ]; uint2 ml[NJ];
#pragma unroll
                for (int j = 0; j < NJ; j++) {
                    a[j] = make_uint4(0, 0, 0, 0); ml[j] = make_uint2(0xff800000u, 0);
                    if (live && c0 + NHW * RPI * j < nct) bad |= 1u << j;
                }
                for (int k = 0; live && s_flushed <= min(h + 1, H - 1); k++) { __nanosleep(X_SLEEP); if (k > (1 << 24)) __trap(); }
                if (threadIdx.x == 32) STAMP(9);
                for (int it = 0;; it++) {
#pragma unroll
                    for (int j = 0; j < NJ; j++) {
                        asm volatile("{ .reg .pred p; setp.ne.u32 p, %6, 0;\n"
                                     "@p ld.relaxed.gpu.global.v4.b32 {%0,%1,%2,%3}, [%7];\n"
                                     "@p ld.relaxed.gpu.global.v2.b32 {%4,%5}, [%8]; }"
                                     : "+r"(a[j].x), "+r"(a[j].y), "+r"(a[j].z), "+r"(a[j].w), "+r"(ml[j].x), "+r"(ml[j].y)
                                     : "r"(bad & (1u << j)), "l"(pa + NHW * RPI * 32 * j), "l"(pm + NHW * RPI * j) : "memory");
                    }
                    uint32_t nb = 0;
#pragma unroll
                    for (int j = NJ - 1; j >= 0; j--) {
                        uint32_t x;
                        asm volatile("{ .reg .b32 u, v;\n"
                            "lop3.b32 u, %1, %2, %7, 0x7e;\n lop3.b32 v, %3, %4, %7, 0x7e;\n lop3.b32 %0, %5, %6, %7, 0x7e;\n"
                            "lop3.b32 %0, %0, u, v, 0xfe; }"
                            : "=r"(x) : "r"(a[j].x), "r"(a[j].y), "r"(a[j].z), "r"(a[j].w), "r"(ml[j].x), "r"(ml[j].y), "r"(tag));
                        nb = nb * 2 + (x & 1);
                    }
                    bad &= nb;
                    if (!__any_sync(0xffffffffu, bad)) break;
                    __nanosleep(X_BACKOFF);
                    if (it > (1 << 22)) __trap();
                }
                if (lane == 0 && mw == 0) STAMP(10);
                float M = Mr;
#pragma unroll
                for (int j = 0; j < NJ; j++) M = fmaxf(M, untag(ml[j].x));
#pragma unroll
                for (int x = 16; x >= LR; x >>= 1) M = fmaxf(M, __shfl_xor_sync(0xffffffffu, M, x));
                const float fr = exp_diff(Mr, M);
                float o0 = 0.f, o1 = 0.f, o2 = 0.f, o3 = 0.f, L = 0.f;
#pragma unroll
                for (int j = 0; j < NJ; j++) {
                    const float e = exp_diff(untag(ml[j].x), M);
                    o0 = fmaf(e, untag(a[j].x), o0); o1 = fmaf(e, untag(a[j].y), o1);
                    o2 = fmaf(e, untag(a[j].z), o2); o3 = fmaf(e, untag(a[j].w), o3);
                    L = fmaf(e, untag(ml[j].y), L);
                }
                float* hb = reinterpret_cast<float*>(smem + OFF_HB) + live * NHW * QW;
                reduce_groups(hb + mw * QW, o0, o1, o2, o3, lane);
#pragma unroll
                for (int x = 16; x >= LR; x >>= 1) L += __shfl_xor_sync(0xffffffffu, L, x);
                if (lane == 0) s_hm[live][mw] = make_float4(M, fmaf(fr, Lr, L), fr, fr * Zr);
                asm volatile("bar.sync 3, %0;" ::"n"(NHW * 32) : "memory");
                float MM = NEG_INF, LL = 0.f, base = 0.f, g[NHW];
                const int col = (mw * 32 + lane) & (QW - 1);
#pragma unroll
                for (int w = 0; w < NHW; w++) MM = fmaxf(MM, s_hm[live][w].x);
#pragma unroll
                for (int w = 0; w < NHW; w++) {
                    const float4 x = s_hm[live][w];
                    const float e = exp_diff(x.x, MM);
                    LL = fmaf(e, x.y, LL);
                    base = fmaf(e, hb[w * QW + col] - x.w, base);
                    g[w] = e * x.z;
                }
                const float inv = __frcp_rn(LL);
                base *= inv;
#pragma unroll
                for (int w = 0; w < NHW; w++) g[w] *= inv;
                if (threadIdx.x == 32 && live) STAMP(5);
                if (mw == 0) {
                    __nv_bfloat16* po = out + h * D + col0 + lane;
                    uint32_t ta = sbase + OFF_TR + lane * 4;
                    asm volatile("{ .reg .pred p; setp.ne.u32 p, %7, 0; @p bar.sync 4, %8; }"
                                 : "+l"(po), "+r"(ta), "+f"(base), "+f"(g[0]), "+f"(g[1]), "+f"(g[2]), "+f"(g[3])
                                 : "r"(live), "n"((1 + NCW) * 32) : "memory");
                    float y0 = base, y1 = 0.f;
#pragma unroll
                    for (int w = 0; w < NCW; w += 2) {
                        y0 = fmaf(g[w % NHW], __uint_as_float(lds32(ta + w * QW * 4)), y0);
                        y1 = fmaf(g[(w + 1) % NHW], __uint_as_float(lds32(ta + (w + 1) * QW * 4)), y1);
                    }
                    asm volatile("{ .reg .pred p; .reg .b16 t; setp.ne.u32 p, %2, 0; cvt.rn.bf16.f32 t, %1; @p st.global.b16 [%0], t; }"
                                 ::"l"(po), "f"(y0 + y1), "r"(live) : "memory");
                }
                if (live && o + nct < NOWN) asm volatile("bar.sync 3, %0;" ::"n"(NHW * 32) : "memory");
                if (live) break;
            }
            if (o == NOWN - 1 && threadIdx.x == 32) ticket[32] = s_epoch + 1;
        }
        if (threadIdx.x == 32) STAMP(6);
    } else {
        const int cw = warp - 1 - NHW;
        const int hw = lane >> 4, li = lane & 15;
        int s = 0, ph = 0;
#pragma unroll 1
        for (uint32_t live = opaque_zero();; live++) {
        if (live) {
        asm volatile("bar.sync 2, %0;" ::"n"(NTHREADS - 32) : "memory");
        const uint32_t tag = (s_epoch + 1) & 1;
        mbar_wait(smem_u32(&s_qbar), 0);
        if (threadIdx.x == NTHREADS - 32) STAMP(1);
        int cur = stream_head(blockIdx.x), nflush = 0, qh = -1;
        if (cw == 0) for (int e = 0; e < cur; e++) publish(sc, e, lane, make_float4(0, 0, 0, 0), NEG_INF, 0.f, tag);
        float4 qlo, qhi;
        while (true) {
            float m = NEG_INF, lsum = 0.f, zsum = 0.f;
            float acc0 = 0.f, acc1 = 0.f, acc2 = 0.f, acc3 = 0.f;
            int nh;
            do {
                mbar_wait(smem_u32(&s_full[s]), ph);
                const int meta = s_meta[s];
                nh = meta & 255;
                if (((meta >> 8) & 255) != qh) {
                    qh = (meta >> 8) & 255;
                    const uint2 l = lds64(sbase + OFF_Q + qh * 256 + li * 8), h = lds64(sbase + OFF_Q + qh * 256 + 128 + li * 8);
                    const uint2 cl = lds64(sbase + OFF_QC + li * 8), ch = lds64(sbase + OFF_QC + 128 + li * 8);
                    const uint2 sl = lds64(sbase + OFF_QS + li * 8), sh = lds64(sbase + OFF_QS + 128 + li * 8);
                    const uint32_t rl0 = bf2_sub(bf2_mul(l.x, cl.x), bf2_mul(h.x, sl.x));
                    const uint32_t rl1 = bf2_sub(bf2_mul(l.y, cl.y), bf2_mul(h.y, sl.y));
                    const uint32_t rh0 = bf2_add(bf2_mul(h.x, ch.x), bf2_mul(l.x, sh.x));
                    const uint32_t rh1 = bf2_add(bf2_mul(h.y, ch.y), bf2_mul(l.y, sh.y));
                    qlo = make_float4(bf_lo(rl0), bf_hi(rl0), bf_lo(rl1), bf_hi(rl1));
                    qhi = make_float4(bf_lo(rh0), bf_hi(rh0), bf_lo(rh1), bf_hi(rh1));
                }
                const uint32_t slot = sbase + s * SLOT;
                const int row0 = cw * RPW;
                float dot[RPW / 2];
#pragma unroll
                for (int it = 0; it < RPW / 2; it++) {
                    const int row = row0 + (RPW / 2) * hw + it;
                    const int4 a = lds128(slot + OFF_K + row * 512 + li * 16);
                    const int4 b = lds128(slot + OFF_K + row * 512 + 256 + li * 16);
                    const uint2 cl = lds64(slot + OFF_C + row * 256 + li * 8);
                    const uint2 ch = lds64(slot + OFF_C + row * 256 + 128 + li * 8);
                    const uint2 sl = lds64(slot + OFF_S + row * 256 + li * 8);
                    const uint2 sh = lds64(slot + OFF_S + row * 256 + 128 + li * 8);
                    const uint32_t sc = lds32(slot + OFF_KS + row * 4);
                    const uint32_t zc = lds32(slot + OFF_KZ + row * 4);
                    const uint32_t s0 = __byte_perm(sc, 0, 0x1010), s1 = __byte_perm(sc, 0, 0x3232);
                    const uint32_t z0 = __byte_perm(zc, 0, 0x1010), z1 = __byte_perm(zc, 0, 0x3232);
                    const uint32_t l0 = bf2_mul(bf2_sub(bf2_pack((float)a.x, (float)a.y), z0), s0);
                    const uint32_t l1 = bf2_mul(bf2_sub(bf2_pack((float)a.z, (float)a.w), z0), s0);
                    const uint32_t h0 = bf2_mul(bf2_sub(bf2_pack((float)b.x, (float)b.y), z1), s1);
                    const uint32_t h1 = bf2_mul(bf2_sub(bf2_pack((float)b.z, (float)b.w), z1), s1);
                    const uint32_t rl0 = bf2_sub(bf2_mul(l0, cl.x), bf2_mul(h0, sl.x));
                    const uint32_t rl1 = bf2_sub(bf2_mul(l1, cl.y), bf2_mul(h1, sl.y));
                    const uint32_t rh0 = bf2_add(bf2_mul(h0, ch.x), bf2_mul(l0, sh.x));
                    const uint32_t rh1 = bf2_add(bf2_mul(h1, ch.y), bf2_mul(l1, sh.y));
                    float d0 = qlo.x * bf_lo(rl0), d1 = qhi.x * bf_lo(rh0);
                    float d2 = qlo.z * bf_lo(rl1), d3 = qhi.z * bf_lo(rh1);
                    d0 = fmaf(qlo.y, bf_hi(rl0), d0); d1 = fmaf(qhi.y, bf_hi(rh0), d1);
                    d2 = fmaf(qlo.w, bf_hi(rl1), d2); d3 = fmaf(qhi.w, bf_hi(rh1), d3);
                    dot[it] = (d0 + d1) + (d2 + d3);
                }
                int4 v[RPW];
#pragma unroll
                for (int r = 0; r < RPW; r++) v[r] = lds128(slot + OFF_V + (row0 + r) * 512 + lane * 16);
                constexpr int LPR = 32 / RPW;
                const int myrow = row0 + lane / LPR;
                const uint32_t vsb = lds16(slot + OFF_VS + myrow * 4 + (lane & 1) * 2);
                const uint32_t vzb = lds16(slot + OFF_VZ + myrow * 4 + (lane & 1) * 2);
                const float vsc = __uint_as_float(vsb << 16), vzc = __uint_as_float(vzb << 16);
                __syncwarp();
                if (lane == 0) mbar_arrive(smem_u32(&s_empty[s]));
                if (++s == NST) { s = 0; ph ^= 1; }
                float t;
                if (RPW == 4) {
                    const bool up = lane & 8;
                    t = (up ? dot[RPW / 2 - 1] : dot[0]) + __shfl_xor_sync(0xffffffffu, up ? dot[0] : dot[RPW / 2 - 1], 8);
                } else {
                    t = dot[0] + __shfl_xor_sync(0xffffffffu, dot[0], 8);
                }
                t += __shfl_xor_sync(0xffffffffu, t, 4);
                t += __shfl_xor_sync(0xffffffffu, t, 2);
                t += __shfl_xor_sync(0xffffffffu, t, 1);
                const float lg = bf_round(bf_round(t) * 0.08838834764831845f);
                if (meta >> 16) {
                    if ((lane & (LPR - 1)) < 2)
                        asm volatile("{ .reg .b64 t; mov.b64 t, {%1, %2}; st.relaxed.gpu.global.b64 [%0], t; }"
                                     ::"l"(sc->row + (qh * 2 + (lane & 1)) * R + ((meta >> 16) - 1) * P + myrow),
                                     "r"(__float_as_uint(lg) | tag), "r"(vsb << 16 | vzb) : "memory");
                    continue;
                }
                float mx = fmaxf(lg, __shfl_xor_sync(0xffffffffu, lg, 16));
                if (RPW == 4) mx = fmaxf(mx, __shfl_xor_sync(0xffffffffu, mx, 8));
                const float mn = fmaxf(m, mx);
                const float alpha = exp_diff(m, mn);
                const float p = exp_diff(lg, mn);
                m = mn;
                const float c = p * vsc;
                lsum = fmaf(lsum, alpha, p);
                zsum = fmaf(zsum, alpha, c * vzc);
                acc0 *= alpha; acc1 *= alpha; acc2 *= alpha; acc3 *= alpha;
#pragma unroll
                for (int r = 0; r < RPW; r++) {
                    const float cr = __shfl_sync(0xffffffffu, c, LPR * r + hw);
                    acc0 = fmaf(cr, (float)v[r].x, acc0);
                    acc1 = fmaf(cr, (float)v[r].y, acc1);
                    acc2 = fmaf(cr, (float)v[r].z, acc2);
                    acc3 = fmaf(cr, (float)v[r].w, acc3);
                }
            } while (nh == cur);

            float* red = reinterpret_cast<float*>(smem + OFF_RED) + (nflush & 1) * NCW * RED_STRIDE;
            float l = lsum + __shfl_xor_sync(0xffffffffu, lsum, 16);
            float z = zsum + __shfl_xor_sync(0xffffffffu, zsum, 16);
            if (RPW == 4) { l += __shfl_xor_sync(0xffffffffu, l, 8); z += __shfl_xor_sync(0xffffffffu, z, 8); }
            z = __shfl_sync(0xffffffffu, z, hw);
            *reinterpret_cast<float4*>(red + cw * RED_STRIDE + 4 * lane) = make_float4(acc0 - z, acc1 - z, acc2 - z, acc3 - z);
            if (lane == 0) *reinterpret_cast<float2*>(red + cw * RED_STRIDE + D) = make_float2(m, l);
            asm volatile("bar.sync 1, %0;" ::"n"(NCW * 32) : "memory");
            if (cw == (nflush & (NCW - 1))) {
                float2 ml[NCW]; float M = NEG_INF;
#pragma unroll
                for (int w = 0; w < NCW; w++) { ml[w] = *reinterpret_cast<const float2*>(red + w * RED_STRIDE + D); M = fmaxf(M, ml[w].x); }
                float4 a = make_float4(0, 0, 0, 0); float L = 0.f;
#pragma unroll
                for (int w = 0; w < NCW; w++) {
                    const float e = exp_diff(ml[w].x, M);
                    const float4 t = *reinterpret_cast<const float4*>(red + w * RED_STRIDE + 4 * lane);
                    a.x += e * t.x; a.y += e * t.y; a.z += e * t.z; a.w += e * t.w;
                    L += e * ml[w].y;
                }
                publish(sc, cur, lane, a, M, L, tag);
                for (int e = cur + 1; e < nh; e++) publish(sc, e, lane, make_float4(0, 0, 0, 0), NEG_INF, 0.f, tag);
                if (lane == 0) s_flushed = nh;
            }
            nflush++;
            if (nh >= H) break;
            cur = nh;
        }

        }
        uint32_t wph = 0;
#pragma unroll 1
        for (int o = blockIdx.x; o < NOWN; o += nct) {
            float o0 = 0.f, o1 = 0.f;
            if (live) mbar_wait(smem_u32(&s_wbar), wph);
            wph ^= 1;
            uint32_t ta = sbase + OFF_TR + (cw * QW + lane) * 4;
#pragma unroll 1
            for (int t = live ? cw / NHW : NT - 1; t < NT; t += NQ) {
                int4 c[HROWS / 4];
#pragma unroll
                for (int k = 0; k < HROWS / 4; k++) c[k] = lds128(sbase + OFF_W + (t * TROWS + (cw & (NHW - 1)) * HROWS + 4 * k) * 4);
                const uint32_t ts = (s + t / 2) % NST;
                uint32_t va = sbase + ts * SLOT + (t & 1) * T_BYTES + ((cw & (NHW - 1)) * HROWS * QW + lane) * 4, eb = smem_u32(&s_empty[ts]);
                asm volatile("" : "+r"(va), "+r"(eb), "+r"(ta));
                if (live) mbar_wait(smem_u32(&s_tile[t]), wph ^ 1);
                if (lane == 0 && (cw & (NHW - 1)) == 0 && t == NT - 1 && live) STAMP(7);
                int v[HROWS];
#pragma unroll
                for (int k = 0; k < HROWS; k++) v[k] = lds32(va + k * QW * 4);
#pragma unroll
                for (int k = 0; k < HROWS / 4; k++) {
                    o0 = fmaf(__int_as_float(c[k].x), (float)v[4 * k], o0);
                    o1 = fmaf(__int_as_float(c[k].y), (float)v[4 * k + 1], o1);
                    o0 = fmaf(__int_as_float(c[k].z), (float)v[4 * k + 2], o0);
                    o1 = fmaf(__int_as_float(c[k].w), (float)v[4 * k + 3], o1);
                }
                if (t + 2 * NST < NT || o + nct < NOWN) {
                    __syncwarp();
                    if (lane == 0 && live) mbar_arrive(eb);
                }
            }
            asm volatile("{ .reg .pred p; setp.ne.u32 p, %0, 0; st.shared.f32 [%2], %3; @p bar.arrive 4, %1; }"
                         ::"r"(live), "n"((1 + NCW) * 32), "r"(ta), "f"(o0 + o1) : "memory");
            if (live) s = (s + NT / 2) % NST;
        }
        if (live) break;
        }
    }
}

}
extern "C" void kernel_launch(void* const* d_in, const int* in_sizes, int n_in, void* d_out, int out_size) {
    typedef CUresult (*EncodeFn)(CUtensorMap*, CUtensorMapDataType, cuuint32_t, void*, const cuuint64_t*, const cuuint64_t*,
                                 const cuuint32_t*, const cuuint32_t*, CUtensorMapInterleave, CUtensorMapSwizzle,
                                 CUtensorMapL2promotion, CUtensorMapFloatOOBfill);
    static int nsm = 0;
    static EncodeFn encode = nullptr;
    static Scratch* sc = nullptr;
    if (nsm == 0) {
        int dev = 0;
        cudaGetDevice(&dev);
        cudaDeviceGetAttribute(&nsm, cudaDevAttrMultiProcessorCount, dev);
        if (nsm > MAXCTA) nsm = MAXCTA;
        cudaFuncSetAttribute(kv_decode_kernel, cudaFuncAttributeMaxDynamicSharedMemorySize, SMEM_BYTES);
        cudaGetSymbolAddress((void**)&sc, g_scratch);
        cudaDriverEntryPointQueryResult qr;
        cudaGetDriverEntryPoint("cuTensorMapEncodeTiled", (void**)&encode, cudaEnableDefault, &qr);
    }
    CUtensorMap vmap;
    const cuuint64_t gdim[2] = {(cuuint64_t)D, (cuuint64_t)H * S};
    const cuuint64_t gstr[1] = {(cuuint64_t)D * 4};
    const cuuint32_t box[2] = {(cuuint32_t)QW, (cuuint32_t)TROWS};
    const cuuint32_t estr[2] = {1, 1};
    encode(&vmap, CU_TENSOR_MAP_DATA_TYPE_INT32, 2, d_in[4], gdim, gstr, box, estr, CU_TENSOR_MAP_INTERLEAVE_NONE,
           CU_TENSOR_MAP_SWIZZLE_NONE, CU_TENSOR_MAP_L2_PROMOTION_NONE, CU_TENSOR_MAP_FLOAT_OOB_FILL_NONE);
    kv_decode_kernel<<<nsm, NTHREADS, SMEM_BYTES>>>(
        (const int*)d_in[1], (const int*)d_in[4], (const __nv_bfloat16*)d_in[9], (const __nv_bfloat16*)d_in[10],
        sc->ticket, nsm,
        (const __nv_bfloat16*)d_in[2], (const __nv_bfloat16*)d_in[3], (const __nv_bfloat16*)d_in[5],
        (const __nv_bfloat16*)d_in[6], (const __nv_bfloat16*)d_in[0], (const __nv_bfloat16*)d_in[7],
        (const __nv_bfloat16*)d_in[8], (__nv_bfloat16*)d_out, sc, vmap);
}
```

```cpp
#include <cuda_runtime.h>
#include <cuda.h>
#include <cuda_bf16.h>
#include <stdint.h>
#include <stddef.h>

namespace {

constexpr int H = 32, S = 8192, D = 128;
constexpr int NCW = 8, NHW = 4;
constexpr int NTHREADS = (1 + NHW + NCW) * 32;
constexpr int P = 16, NST = 8;
constexpr int KLIM = 12;
constexpr int BPH = S / P;
constexpr int NITEMS = BPH * H;
constexpr int RPW = P / NCW;
constexpr int MAXCTA = 144;
static_assert(RPW == 2, "rows per warp");
constexpr int SPF = 64, SPA = 1024;

constexpr int QW = 32, OPH = D / QW, NOWN = H * OPH;
constexpr int LR = QW / 4, RPI = 32 / LR;
static_assert(RPI == 4, "merge layout");
constexpr uint32_t T_BYTES = 8192;
constexpr int NT = 16, TROWS = T_BYTES / (QW * 4), R = NT * TROWS;
constexpr int NFREE = 2;
constexpr int NQ = NCW / NHW;
constexpr uint32_t HK = R / P;
constexpr int HROWS = TROWS / NHW;
constexpr int NW = (NT * HROWS + 31) / 32;
constexpr int NJ = (MAXCTA + NHW * RPI - 1) / (NHW * RPI);
static_assert(NT % 2 == 0 && NQ == 2 && R % P == 0 && R < S && NST <= 8, "held-back rows");

constexpr uint32_t KV_BYTES = P * D * 4;
constexpr uint32_t CS_BYTES = P * D * 2;
constexpr uint32_t SC_BYTES = P * 4;
constexpr uint32_t OFF_K = 0, OFF_V = KV_BYTES, OFF_C = 2 * KV_BYTES, OFF_S = OFF_C + CS_BYTES;
constexpr uint32_t OFF_KS = OFF_S + CS_BYTES, OFF_KZ = OFF_KS + SC_BYTES, OFF_VS = OFF_KZ + SC_BYTES,
                   OFF_VZ = OFF_VS + SC_BYTES;
constexpr uint32_t SLOT_TX = OFF_VZ + SC_BYTES;
constexpr uint32_t SLOT = (SLOT_TX + 127) / 128 * 128;
constexpr uint32_t OFF_Q = NST * SLOT;
constexpr uint32_t OFF_QC = OFF_Q + H * D * 2, OFF_QS = OFF_QC + D * 2;
constexpr uint32_t Q_TX = H * D * 2 + 2 * D * 2;
constexpr uint32_t OFF_RED = OFF_Q + Q_TX;
constexpr uint32_t RED_STRIDE = D + 4;
constexpr uint32_t OFF_W = OFF_RED + 2 * NCW * RED_STRIDE * 4;
constexpr uint32_t OFF_TR = OFF_W + R * 4;
constexpr uint32_t OFF_HB = OFF_TR + NCW * QW * 4;
constexpr uint32_t SMEM_BYTES = OFF_HB + 2 * NHW * QW * 4;

struct Scratch {
    float4 acc[H * MAXCTA * 32];
    float2 ml[H * MAXCTA];
    uint2 row[H * 2 * R];
    alignas(128) unsigned int ticket[64];
};
__device__ Scratch g_scratch;

__device__ __forceinline__ uint32_t smem_u32(const void* p) { return (uint32_t)__cvta_generic_to_shared(p); }
__device__ __forceinline__ bool elect_one() {
    uint32_t p;
    asm volatile("{ .reg .pred p; elect.sync _|p, 0xffffffff; selp.u32 %0, 1, 0, p; }" : "=r"(p));
    return p;
}
__device__ __forceinline__ uint32_t opaque_zero() {
    uint32_t z;
    asm volatile("mov.u32 %0, 0;" : "=r"(z));
    return z;
}
__device__ __forceinline__ uint32_t clock32() {
    uint32_t c;
    asm volatile("mov.u32 %0, %clock;" : "=r"(c));
    return c;
}
__device__ __forceinline__ void mbar_init(uint32_t bar, uint32_t cnt) {
    asm volatile("mbarrier.init.shared.b64 [%0], %1;" ::"r"(bar), "r"(cnt) : "memory");
}
__device__ __forceinline__ void mbar_expect_tx(uint32_t bar, uint32_t bytes) {
    asm volatile("mbarrier.arrive.expect_tx.shared.b64 _, [%0], %1;" ::"r"(bar), "r"(bytes) : "memory");
}
__device__ __forceinline__ void mbar_arrive(uint32_t bar) {
    asm volatile("mbarrier.arrive.shared.b64 _, [%0];" ::"r"(bar) : "memory");
}
__device__ __forceinline__ void mbar_wait(uint32_t bar, uint32_t parity) {
    uint32_t done;
    int it = 0;
    do {
        asm volatile("{ .reg .pred p; mbarrier.try_wait.parity.shared.b64 p, [%1], %2; selp.u32 %0, 1, 0, p; }"
                     : "=r"(done) : "r"(bar), "r"(parity) : "memory");
        if (++it > (1 << 24)) __trap();
    } while (!done);
}
__device__ __forceinline__ void bulk_g2s(uint32_t dst, const void* src, uint32_t bytes, uint32_t bar) {
    asm volatile("cp.async.bulk.shared::cluster.global.mbarrier::complete_tx::bytes [%0], [%1], %2, [%3];"
                 ::"r"(dst), "l"(src), "r"(bytes), "r"(bar) : "memory");
}
__device__ __forceinline__ void bulk_g2s_hint(uint32_t dst, const void* src, uint32_t bytes, uint32_t bar, uint64_t pol) {
    asm volatile("cp.async.bulk.shared::cluster.global.mbarrier::complete_tx::bytes.L2::cache_hint [%0], [%1], %2, [%3], %4;"
                 ::"r"(dst), "l"(src), "r"(bytes), "r"(bar), "l"(pol) : "memory");
}
__device__ __forceinline__ int4 lds128(uint32_t a) {
    int4 v;
    asm volatile("ld.shared.v4.s32 {%0,%1,%2,%3}, [%4];" : "=r"(v.x), "=r"(v.y), "=r"(v.z), "=r"(v.w) : "r"(a));
    return v;
}
__device__ __forceinline__ uint2 lds64(uint32_t a) {
    uint2 v;
    asm volatile("ld.shared.v2.u32 {%0,%1}, [%2];" : "=r"(v.x), "=r"(v.y) : "r"(a));
    return v;
}
__device__ __forceinline__ uint32_t lds32(uint32_t a) {
    uint32_t v;
    asm volatile("ld.shared.u32 %0, [%1];" : "=r"(v) : "r"(a));
    return v;
}
__device__ __forceinline__ uint32_t lds16(uint32_t a) {
    uint16_t v;
    asm volatile("ld.shared.u16 %0, [%1];" : "=h"(v) : "r"(a));
    return v;
}
__device__ __forceinline__ uint32_t bf2_mul(uint32_t a, uint32_t b) {
    uint32_t d; asm("mul.rn.bf16x2 %0, %1, %2;" : "=r"(d) : "r"(a), "r"(b)); return d;
}
__device__ __forceinline__ uint32_t bf2_add(uint32_t a, uint32_t b) {
    uint32_t d; asm("add.rn.bf16x2 %0, %1, %2;" : "=r"(d) : "r"(a), "r"(b)); return d;
}
__device__ __forceinline__ uint32_t bf2_sub(uint32_t a, uint32_t b) {
    uint32_t d; asm("sub.rn.bf16x2 %0, %1, %2;" : "=r"(d) : "r"(a), "r"(b)); return d;
}
__device__ __forceinline__ uint32_t bf2_pack(float lo, float hi) {
    uint32_t d; asm("cvt.rn.bf16x2.f32 %0, %1, %2;" : "=r"(d) : "f"(hi), "f"(lo)); return d;
}
__device__ __forceinline__ float bf_lo(uint32_t v) { return __uint_as_float(v << 16); }
__device__ __forceinline__ float bf_hi(uint32_t v) { return __uint_as_float(v & 0xffff0000u); }
__device__ __forceinline__ float bf_round(float x) { return __bfloat162float(__float2bfloat16_rn(x)); }
__device__ __forceinline__ float ex2(float x) { float y; asm("ex2.approx.ftz.f32 %0, %1;" : "=f"(y) : "f"(x)); return y; }

constexpr float LOG2E = 1.4426950408889634f;
constexpr float NEG_INF = -__builtin_huge_valf();

__device__ __forceinline__ float exp_diff(float a, float b) {
    return (a == NEG_INF) ? 0.f : ex2((a - b) * LOG2E);
}

__device__ __forceinline__ uint32_t tagw(float x, uint32_t tag) { return (__float_as_uint(x) & ~1u) | tag; }
__device__ __forceinline__ float untag(uint32_t x) { return __uint_as_float(x & ~1u); }
__device__ __forceinline__ void publish(Scratch* sc, int h, int lane, float4 a, float M, float L, uint32_t tag) {
    float4* pa = sc->acc + (size_t)(h * MAXCTA + blockIdx.x) * 32 + lane;
    asm volatile("st.relaxed.gpu.global.v4.b32 [%0], {%1,%2,%3,%4};" ::"l"(pa), "r"(tagw(a.x, tag)), "r"(tagw(a.y, tag)),
                 "r"(tagw(a.z, tag)), "r"(tagw(a.w, tag)) : "memory");
    if (lane == 0)
        asm volatile("st.relaxed.gpu.global.v2.b32 [%0], {%1,%2};" ::"l"(sc->ml + h * MAXCTA + blockIdx.x),
                     "r"(tagw(M, tag)), "r"(tagw(L, tag)) : "memory");
}

__device__ __forceinline__ void reduce_groups(float* dst, float o0, float o1, float o2, float o3, int lane) {
    const bool hi = lane & 16;
    const float r0 = (hi ? o2 : o0) + __shfl_xor_sync(0xffffffffu, hi ? o0 : o2, 16);
    const float r1 = (hi ? o3 : o1) + __shfl_xor_sync(0xffffffffu, hi ? o1 : o3, 16);
    dst += (lane & (LR - 1)) * 4 + hi * 2;
    const bool up = lane & 8;
    dst[up] = (up ? r1 : r0) + __shfl_xor_sync(0xffffffffu, up ? r0 : r1, 8);
}

__host__ __device__ constexpr uint32_t held0(uint32_t h) { return 124 + (int)h * -4; }
constexpr uint32_t W0 = 8448, LAST0 = (H - 1) * BPH + held0(H - 1);
__device__ __forceinline__ uint32_t item_index(uint32_t i) {
    return i - W0 < HK ? LAST0 + i - W0 : i - W0 < LAST0 + HK - W0 ? i - HK : i;
}
__device__ __forceinline__ uint32_t stream_head(uint32_t i) {
    return i - W0 < HK ? W0 / BPH : min(item_index(i) / BPH, (uint32_t)H);
}

__global__ void __launch_bounds__(NTHREADS, 1)
kv_decode_kernel(const int* __restrict__ qk, const int* __restrict__ qv,
                 const __nv_bfloat16* __restrict__ k_cos, const __nv_bfloat16* __restrict__ k_sin,
                 unsigned int* __restrict__ ticket, const uint32_t nct,
                 const __nv_bfloat16* __restrict__ ks, const __nv_bfloat16* __restrict__ kz,
                 const __nv_bfloat16* __restrict__ vs, const __nv_bfloat16* __restrict__ vz,
                 const __nv_bfloat16* __restrict__ q, const __nv_bfloat16* __restrict__ q_cos,
                 const __nv_bfloat16* __restrict__ q_sin, __nv_bfloat16* __restrict__ out, Scratch* __restrict__ sc,
                 const __grid_constant__ CUtensorMap vmap) {
    extern __shared__ __align__(128) unsigned char smem[];
    __shared__ __align__(8) uint64_t s_full[NST], s_empty[NST], s_qbar, s_wbar, s_tile[NT];
    __shared__ volatile int s_meta[NST];
    __shared__ volatile int s_tick;
    __shared__ volatile int s_flushed;
    __shared__ float4 s_hm[2][NHW];
    __shared__ uint32_t s_epoch;
    const uint32_t sbase = smem_u32(smem);
    uint64_t pol;
    asm("createpolicy.fractional.L2::evict_first.b64 %0, 1.0;" : "=l"(pol));
    const bool leader = elect_one();
    static_assert(2 * MAXCTA <= BPH, "first item");
    uint32_t c0;
    if (threadIdx.x < 32 && leader) {
        const uint32_t bar = smem_u32(&s_full[0]);
        mbar_init(bar, 1);
        asm volatile("fence.mbarrier_init.release.cluster;" ::: "memory");
        uint32_t ofs;
        asm volatile("mov.u32 %0, %ctaid.x;" : "=r"(ofs));
        const bool held = ofs - held0(0) < HK;
        ofs *= P * D;
        mbar_expect_tx(bar, (held ? KV_BYTES : 2 * KV_BYTES) + 2 * CS_BYTES);
        c0 = clock32();
        bulk_g2s_hint(sbase + OFF_K, qk + ofs, KV_BYTES, bar, pol);
        if (!held) bulk_g2s_hint(sbase + OFF_V, qv + ofs, KV_BYTES, bar, pol);
        bulk_g2s(sbase + OFF_C, k_cos + ofs, CS_BYTES, bar);
        bulk_g2s(sbase + OFF_S, k_sin + ofs, CS_BYTES, bar);
    }
    __syncwarp();
    constexpr int KU = KV_BYTES / 4096, NPRE = KLIM / (2 * KU);
    const uint32_t tbase = NPRE * nct, twrap = NITEMS - tbase + nct - 1;
    uint32_t epoch, pend;
    asm volatile("{ .reg .pred p; setp.ne.u32 p, %4, 0;\n"
                 "@p atom.relaxed.gpu.global.inc.u32 %0, [%2], %3;\n"
                 "@p ld.relaxed.gpu.global.u32 %1, [%2 + 128]; }"
                 : "=r"(pend), "=r"(epoch) : "l"(ticket), "r"(twrap), "r"((uint32_t)(leader && threadIdx.x >> 5 == 1)) : "memory");
    const int warp = __shfl_sync(0xffffffffu, threadIdx.x >> 5, 0), lane = threadIdx.x & 31;
    static_assert(NPRE >= 2 && KLIM <= NST * KU && W0 >= 2 * MAXCTA && MAXCTA <= BPH, "static items");
    auto meta = [&](uint32_t idx, uint32_t nhead) {
        const uint32_t hb = (idx & (BPH - 1)) - held0(idx / BPH);
        return nhead | idx / BPH << 8 | (hb < HK ? (hb + 1) << 16 : 0);
    };
    if (leader) {
        if (warp < NST) {
            if (warp == 0) {
                s_meta[0] = meta(blockIdx.x, 0);
                s_tick = -1;
            } else {
                mbar_init(smem_u32(&s_full[warp]), 1);
            }
            mbar_init(smem_u32(&s_empty[warp]), NCW);
            asm volatile("fence.mbarrier_init.release.cluster;" ::: "memory");
        } else if (warp == NST) {
            const uint32_t bar = smem_u32(&s_qbar);
            mbar_init(bar, 1);
            asm volatile("fence.mbarrier_init.release.cluster;" ::: "memory");
            mbar_expect_tx(bar, Q_TX + 4 * SC_BYTES);
            bulk_g2s_hint(sbase + OFF_KS, ks + blockIdx.x * (P * 2), SC_BYTES, bar, pol);
            bulk_g2s_hint(sbase + OFF_KZ, kz + blockIdx.x * (P * 2), SC_BYTES, bar, pol);
            bulk_g2s_hint(sbase + OFF_VS, vs + blockIdx.x * (P * 2), SC_BYTES, bar, pol);
            bulk_g2s_hint(sbase + OFF_VZ, vz + blockIdx.x * (P * 2), SC_BYTES, bar, pol);
            bulk_g2s(sbase + OFF_Q, q, H * D * 2, bar);
            bulk_g2s(sbase + OFF_QC, q_cos, D * 2, bar);
            bulk_g2s(sbase + OFF_QS, q_sin, D * 2, bar);
            mbar_init(smem_u32(&s_wbar), NHW);
        } else if (warp == NST + 1) {
            for (int t = 0; t < NT; t++) mbar_init(smem_u32(&s_tile[t]), 1);
            asm volatile("fence.mbarrier_init.release.cluster;" ::: "memory");
        } else if (warp == NST + 2) {
            asm volatile("prefetch.tensormap [%0];" ::"l"(&vmap) : "memory");
        }
    }
    __syncthreads();

    if (warp == 0) {
        if (leader) {
            unsigned int* const tk = ticket + (threadIdx.x >> 5);
            int s = 1, ph = 1, cnt = 1;
            int ls = 0, lph = 0, fl = blockIdx.x - held0(0) < HK ? KU : 2 * KU;
            uint32_t cost = fl;
            uint32_t cur = blockIdx.x + nct, nxt = cur + nct;
            uint32_t creq = c0, cgood = c0, vgood = 0;
#pragma unroll 1
            for (uint32_t live = opaque_zero();; live++) {
                do {
                    const uint32_t idx = item_index(cur);
                    const int c = (idx & (BPH - 1)) - held0(idx / BPH) < HK ? KU : 2 * KU;
                    if (cnt >= NST) mbar_wait(smem_u32(&s_empty[s]), ph);
                    const uint32_t bar = smem_u32(&s_full[s]), dst = sbase + s * SLOT;
                    asm volatile("mbarrier.expect_tx.relaxed.cta.shared::cta.b64 [%0], %1;"
                                 ::"r"(bar), "r"(c == KU ? SLOT_TX - KV_BYTES : SLOT_TX) : "memory");
                    bulk_g2s(dst + OFF_C, k_cos + (idx & (BPH - 1)) * (P * D), CS_BYTES, bar);
                    bulk_g2s(dst + OFF_S, k_sin + (idx & (BPH - 1)) * (P * D), CS_BYTES, bar);
                    bulk_g2s_hint(dst + OFF_KS, ks + idx * (P * 2), SC_BYTES, bar, pol);
                    bulk_g2s_hint(dst + OFF_KZ, kz + idx * (P * 2), SC_BYTES, bar, pol);
                    bulk_g2s_hint(dst + OFF_VS, vs + idx * (P * 2), SC_BYTES, bar, pol);
                    bulk_g2s_hint(dst + OFF_VZ, vz + idx * (P * 2), SC_BYTES, bar, pol);
                    fl += c;
                    while (fl > KLIM) {
                        mbar_wait(smem_u32(&s_full[ls]), lph);
                        fl -= (cost >> 4 * ls) & 15;
                        if (++ls == NST) { ls = 0; lph ^= 1; }
                    }
                    bulk_g2s_hint(dst + OFF_K, qk + (size_t)idx * (P * D), KV_BYTES, bar, pol);
                    if (c != KU) bulk_g2s_hint(dst + OFF_V, qv + (size_t)idx * (P * D), KV_BYTES, bar, pol);
                    cost = (cost & ~(15u << 4 * s)) | c << 4 * s;
                    cnt++;
                    if (cnt == NPRE) for (int k = 0; (int)(pend = s_tick) < 0; k++) if (k > (1 << 24)) __trap();
                    nxt = cnt < NPRE ? cur + nct : pend + tbase;
                    if (cnt >= NPRE && nxt < (uint32_t)NITEMS) {
                        asm volatile("atom.relaxed.gpu.global.inc.u32 %0, [%1], %2;" : "=r"(pend) : "l"(tk), "r"(twrap) : "memory");
                        cgood = creq; vgood = nxt; creq = clock32();
                        if ((idx & (SPF - 1)) < 4 && idx + SPA < NITEMS) {
                            const __nv_bfloat16* p = (idx & 2) ? ((idx & 1) ? vz : vs) : ((idx & 1) ? kz : ks);
                            asm volatile("cp.async.bulk.prefetch.L2.global.L2::cache_hint [%0], %1, %2;"
                                         ::"l"(p + ((idx & ~(SPF - 1)) + SPA) * (P * 2)), "n"(SPF * SC_BYTES), "l"(pol) : "memory");
                        }
                    }
                    s_meta[s] = meta(idx, stream_head(nxt));
                    mbar_arrive(bar);
                    if (++s == NST) { s = 0; ph ^= 1; }
                    cur = nxt;
                    if (cur >= (uint32_t)NITEMS) break;
                } while (live || cnt < NPRE);
                asm volatile("prefetch.tensormap [%0];" ::"l"(&vmap) : "memory");
                constexpr float STREAM = (float)NITEMS * (2 * KV_BYTES + 4 * SC_BYTES) + 2.f * S * D * 2 - (float)NOWN * NT * T_BYTES;
                const float per_byte = (float)(creq - c0) * (1.f / STREAM);
                const float ip = per_byte * (2 * KV_BYTES + 4 * SC_BYTES), tp = per_byte * (float)(min(nct, (uint32_t)NOWN) * T_BYTES);
                const uint32_t step = tp;
                uint32_t dl = cgood + (uint32_t)(ip * (nct * 1.9f + (float)(NITEMS - vgood))) + (blockIdx.x / OPH) * step / H;
#pragma unroll 1
                for (int o = blockIdx.x; o < NOWN; o += nct) {
#pragma unroll 1
                    for (int t = live ? 0 : NT - 1; t < NT; t++) {
                        if (live) {
                            for (int k = 0; (int)(clock32() - dl) < 0 && k < (1 << 20); k++);
                            if (t < NT - 1 - NFREE) dl += step;
                            if (!(t & 1)) mbar_wait(smem_u32(&s_empty[s]), ph);
                        }
                        asm volatile("{ .reg .pred p; setp.ne.u32 p, %6, 0;\n"
                                     "@p mbarrier.arrive.expect_tx.shared.b64 _, [%2], %7;\n"
                                     "@p cp.async.bulk.tensor.2d.shared::cluster.global.mbarrier::complete_tx::bytes.L2::cache_hint "
                                     "[%0], [%1, {%3, %4}], [%2], %5; }" ::"r"(sbase + s * SLOT + (t & 1) * T_BYTES), "l"(&vmap), "r"(smem_u32(&s_tile[t])),
                                     "r"((o % OPH) * QW), "r"((o / OPH) * S + held0(o / OPH) * P + t * TROWS), "l"(pol), "r"(live), "n"(T_BYTES) : "memory");
                        if (live && (t & 1) && ++s == NST) { s = 0; ph ^= 1; }
                    }
                }
                if (live) break;
            }
        }
    } else if (warp <= NHW) {
        const int mw = warp - 1;
        if (warp == 1 && leader) { s_tick = pend; s_epoch = epoch; s_flushed = 0; }
        asm volatile("bar.sync 2, %0;" ::"n"(NTHREADS - 32) : "memory");
        const uint32_t tag = (s_epoch + 1) & 1;
        float* sw = reinterpret_cast<float*>(smem + OFF_W);
#pragma unroll 1
        for (int o = blockIdx.x; o < NOWN; o += nct) {
            const int h = o / OPH, col0 = (o % OPH) * QW;
            const uint2* pr = sc->row + (h * 2 + col0 / 64) * R + mw * HROWS;
            const int c0 = mw * RPI + lane / LR;
            const float4* pa = sc->acc + (size_t)(h * MAXCTA + c0) * 32 + col0 / 4 + (lane & (LR - 1));
            const float2* pm = sc->ml + h * MAXCTA + c0;
#pragma unroll 1
            for (uint32_t live = opaque_zero();; live++) {
                uint2 rw[NW];
                uint32_t bad = 0;
#pragma unroll
                for (int j = 0; j < NW; j++) {
                    rw[j] = make_uint2(0xff800000u, 0);
                    if (live && lane + 32 * j < NT * HROWS) bad |= 1u << j;
                }
                for (int k = 0; live && s_flushed <= (h == H - 1 ? min((int)(W0 / BPH) + 1, H - 2) : h); k++) { __nanosleep(64); if (k > (1 << 24)) __trap(); }
                for (int it = 0;; it++) {
#pragma unroll
                    for (int j = 0; j < NW; j++) {
                        const int i = lane + 32 * j;
                        asm volatile("{ .reg .pred p; .reg .b64 t; setp.ne.u32 p, %2, 0; mov.b64 t, {%0, %1};\n"
                                     "@p ld.relaxed.gpu.global.b64 t, [%3]; mov.b64 {%0, %1}, t; }"
                                     : "+r"(rw[j].x), "+r"(rw[j].y)
                                     : "r"(bad & (1u << j)), "l"(pr + i / HROWS * TROWS + i % HROWS) : "memory");
                    }
                    uint32_t nb = 0;
#pragma unroll
                    for (int j = NW - 1; j >= 0; j--) nb = nb * 2 + ((rw[j].x ^ tag) & 1);
                    bad &= nb;
                    if (!__any_sync(0xffffffffu, bad)) break;
                    __nanosleep(400);
                    if (it > (1 << 22)) __trap();
                }
                float Mr = NEG_INF, Lr = 0.f, Zr = 0.f;
#pragma unroll
                for (int j = 0; j < NW; j++) Mr = fmaxf(Mr, untag(rw[j].x));
#pragma unroll
                for (int x = 16; x > 0; x >>= 1) Mr = fmaxf(Mr, __shfl_xor_sync(0xffffffffu, Mr, x));
#pragma unroll
                for (int j = 0; j < NW; j++) {
                    const int i = lane + 32 * j;
                    const float p = exp_diff(untag(rw[j].x), Mr), w = p * bf_hi(rw[j].y);
                    Lr += p;
                    Zr = fmaf(w, bf_lo(rw[j].y), Zr);
                    if (i < NT * HROWS) sw[i / HROWS * TROWS + mw * HROWS + i % HROWS] = w;
                }
                __syncwarp();
                if (lane == 0 && live) mbar_arrive(smem_u32(&s_wbar));
#pragma unroll
                for (int x = 16; x > 0; x >>= 1) { Lr += __shfl_xor_sync(0xffffffffu, Lr, x); Zr += __shfl_xor_sync(0xffffffffu, Zr, x); }
                uint4 a[NJ]; uint2 ml[NJ];
#pragma unroll
                for (int j = 0; j < NJ; j++) {
                    a[j] = make_uint4(0, 0, 0, 0); ml[j] = make_uint2(0xff800000u, 0);
                    if (live && c0 + NHW * RPI * j < nct) bad |= 1u << j;
                }
                for (int k = 0; live && s_flushed <= min(h + 1, H - 1); k++) { __nanosleep(64); if (k > (1 << 24)) __trap(); }
                if (live && h == H - 1) mbar_wait(smem_u32(&s_tile[4]), (o / nct) & 1);
                for (int it = 0;; it++) {
#pragma unroll
                    for (int j = 0; j < NJ; j++) {
                        asm volatile("{ .reg .pred p; setp.ne.u32 p, %6, 0;\n"
                                     "@p ld.relaxed.gpu.global.v4.b32 {%0,%1,%2,%3}, [%7];\n"
                                     "@p ld.relaxed.gpu.global.v2.b32 {%4,%5}, [%8]; }"
                                     : "+r"(a[j].x), "+r"(a[j].y), "+r"(a[j].z), "+r"(a[j].w), "+r"(ml[j].x), "+r"(ml[j].y)
                                     : "r"(bad & (1u << j)), "l"(pa + NHW * RPI * 32 * j), "l"(pm + NHW * RPI * j) : "memory");
                    }
                    uint32_t nb = 0;
#pragma unroll
                    for (int j = NJ - 1; j >= 0; j--) {
                        uint32_t x;
                        asm volatile("{ .reg .b32 u, v;\n"
                            "lop3.b32 u, %1, %2, %7, 0x7e;\n lop3.b32 v, %3, %4, %7, 0x7e;\n lop3.b32 %0, %5, %6, %7, 0x7e;\n"
                            "lop3.b32 %0, %0, u, v, 0xfe; }"
                            : "=r"(x) : "r"(a[j].x), "r"(a[j].y), "r"(a[j].z), "r"(a[j].w), "r"(ml[j].x), "r"(ml[j].y), "r"(tag));
                        nb = nb * 2 + (x & 1);
                    }
                    bad &= nb;
                    if (!__any_sync(0xffffffffu, bad)) break;
                    __nanosleep(100);
                    if (it > (1 << 22)) __trap();
                }
                float M = Mr;
#pragma unroll
                for (int j = 0; j < NJ; j++) M = fmaxf(M, untag(ml[j].x));
#pragma unroll
                for (int x = 16; x >= LR; x >>= 1) M = fmaxf(M, __shfl_xor_sync(0xffffffffu, M, x));
                const float fr = exp_diff(Mr, M);
                float o0 = 0.f, o1 = 0.f, o2 = 0.f, o3 = 0.f, L = 0.f;
#pragma unroll
                for (int j = 0; j < NJ; j++) {
                    const float e = exp_diff(untag(ml[j].x), M);
                    o0 = fmaf(e, untag(a[j].x), o0); o1 = fmaf(e, untag(a[j].y), o1);
                    o2 = fmaf(e, untag(a[j].z), o2); o3 = fmaf(e, untag(a[j].w), o3);
                    L = fmaf(e, untag(ml[j].y), L);
                }
                float* hb = reinterpret_cast<float*>(smem + OFF_HB) + live * NHW * QW;
                reduce_groups(hb + mw * QW, o0, o1, o2, o3, lane);
#pragma unroll
                for (int x = 16; x >= LR; x >>= 1) L += __shfl_xor_sync(0xffffffffu, L, x);
                if (lane == 0) s_hm[live][mw] = make_float4(M, fmaf(fr, Lr, L), fr, fr * Zr);
                asm volatile("bar.sync 3, %0;" ::"n"(NHW * 32) : "memory");
                if (live && o == NOWN - 1 && threadIdx.x == 64) ticket[32] = s_epoch + 1;
                float MM = NEG_INF, LL = 0.f, base = 0.f, g[NHW];
                const int col = (mw * 32 + lane) & (QW - 1);
#pragma unroll
                for (int w = 0; w < NHW; w++) MM = fmaxf(MM, s_hm[live][w].x);
#pragma unroll
                for (int w = 0; w < NHW; w++) {
                    const float4 x = s_hm[live][w];
                    const float e = exp_diff(x.x, MM);
                    LL = fmaf(e, x.y, LL);
                    base = fmaf(e, hb[w * QW + col] - x.w, base);
                    g[w] = e * x.z;
                }
                const float inv = __frcp_rn(LL);
                base *= inv;
#pragma unroll
                for (int w = 0; w < NHW; w++) g[w] *= inv;
                if (mw == 0) {
                    __nv_bfloat16* po = out + h * D + col0 + lane;
                    uint32_t ta = sbase + OFF_TR + lane * 4;
                    asm volatile("{ .reg .pred p; setp.ne.u32 p, %7, 0; @p bar.sync 4, %8; }"
                                 : "+l"(po), "+r"(ta), "+f"(base), "+f"(g[0]), "+f"(g[1]), "+f"(g[2]), "+f"(g[3])
                                 : "r"(live), "n"((1 + NCW) * 32) : "memory");
                    float y0 = base, y1 = 0.f;
#pragma unroll
                    for (int w = 0; w < NCW; w += 2) {
                        y0 = fmaf(g[w % NHW], __uint_as_float(lds32(ta + w * QW * 4)), y0);
                        y1 = fmaf(g[(w + 1) % NHW], __uint_as_float(lds32(ta + (w + 1) * QW * 4)), y1);
                    }
                    asm volatile("{ .reg .pred p; .reg .b16 t; setp.ne.u32 p, %2, 0; cvt.rn.bf16.f32 t, %1; @p st.global.b16 [%0], t; }"
                                 ::"l"(po), "f"(y0 + y1), "r"(live) : "memory");
                }
                if (live && o + nct < NOWN) asm volatile("bar.sync 3, %0;" ::"n"(NHW * 32) : "memory");
                if (live) break;
            }
        }
    } else {
        const int cw = warp - 1 - NHW;
        const int hw = lane >> 4, li = lane & 15;
        int s = 0, ph = 0;
#pragma unroll 1
        for (uint32_t live = opaque_zero();; live++) {
            if (live) {
                asm volatile("bar.sync 2, %0;" ::"n"(NTHREADS - 32) : "memory");
                const uint32_t tag = (s_epoch + 1) & 1;
                mbar_wait(smem_u32(&s_qbar), 0);
                int cur = stream_head(blockIdx.x), nflush = 0, qh = -1;
                if (cw == 0) for (int e = 0; e < cur; e++) publish(sc, e, lane, make_float4(0, 0, 0, 0), NEG_INF, 0.f, tag);
                float4 qlo, qhi;
                while (true) {
                    float m = NEG_INF, lsum = 0.f, zsum = 0.f;
                    float acc0 = 0.f, acc1 = 0.f, acc2 = 0.f, acc3 = 0.f;
                    int nh;
                    do {
                        mbar_wait(smem_u32(&s_full[s]), ph);
                        const int meta = s_meta[s];
                        nh = meta & 255;
                        if (((meta >> 8) & 255) != qh) {
                            qh = (meta >> 8) & 255;
                            const uint2 l = lds64(sbase + OFF_Q + qh * 256 + li * 8), h = lds64(sbase + OFF_Q + qh * 256 + 128 + li * 8);
                            const uint2 cl = lds64(sbase + OFF_QC + li * 8), ch = lds64(sbase + OFF_QC + 128 + li * 8);
                            const uint2 sl = lds64(sbase + OFF_QS + li * 8), sh = lds64(sbase + OFF_QS + 128 + li * 8);
                            const uint32_t rl0 = bf2_sub(bf2_mul(l.x, cl.x), bf2_mul(h.x, sl.x));
                            const uint32_t rl1 = bf2_sub(bf2_mul(l.y, cl.y), bf2_mul(h.y, sl.y));
                            const uint32_t rh0 = bf2_add(bf2_mul(h.x, ch.x), bf2_mul(l.x, sh.x));
                            const uint32_t rh1 = bf2_add(bf2_mul(h.y, ch.y), bf2_mul(l.y, sh.y));
                            qlo = make_float4(bf_lo(rl0), bf_hi(rl0), bf_lo(rl1), bf_hi(rl1));
                            qhi = make_float4(bf_lo(rh0), bf_hi(rh0), bf_lo(rh1), bf_hi(rh1));
                        }
                        const uint32_t slot = sbase + s * SLOT;
                        const int row0 = cw * RPW;
                        float dot;
                        {
                            const int row = row0 + hw;
                            const int4 a = lds128(slot + OFF_K + row * 512 + li * 16);
                            const int4 b = lds128(slot + OFF_K + row * 512 + 256 + li * 16);
                            const uint2 cl = lds64(slot + OFF_C + row * 256 + li * 8);
                            const uint2 ch = lds64(slot + OFF_C + row * 256 + 128 + li * 8);
                            const uint2 sl = lds64(slot + OFF_S + row * 256 + li * 8);
                            const uint2 sh = lds64(slot + OFF_S + row * 256 + 128 + li * 8);
                            const uint32_t sc = lds32(slot + OFF_KS + row * 4);
                            const uint32_t zc = lds32(slot + OFF_KZ + row * 4);
                            const uint32_t s0 = __byte_perm(sc, 0, 0x1010), s1 = __byte_perm(sc, 0, 0x3232);
                            const uint32_t z0 = __byte_perm(zc, 0, 0x1010), z1 = __byte_perm(zc, 0, 0x3232);
                            const uint32_t l0 = bf2_mul(bf2_sub(bf2_pack((float)a.x, (float)a.y), z0), s0);
                            const uint32_t l1 = bf2_mul(bf2_sub(bf2_pack((float)a.z, (float)a.w), z0), s0);
                            const uint32_t h0 = bf2_mul(bf2_sub(bf2_pack((float)b.x, (float)b.y), z1), s1);
                            const uint32_t h1 = bf2_mul(bf2_sub(bf2_pack((float)b.z, (float)b.w), z1), s1);
                            const uint32_t rl0 = bf2_sub(bf2_mul(l0, cl.x), bf2_mul(h0, sl.x));
                            const uint32_t rl1 = bf2_sub(bf2_mul(l1, cl.y), bf2_mul(h1, sl.y));
                            const uint32_t rh0 = bf2_add(bf2_mul(h0, ch.x), bf2_mul(l0, sh.x));
                            const uint32_t rh1 = bf2_add(bf2_mul(h1, ch.y), bf2_mul(l1, sh.y));
                            float d0 = qlo.x * bf_lo(rl0), d1 = qhi.x * bf_lo(rh0);
                            float d2 = qlo.z * bf_lo(rl1), d3 = qhi.z * bf_lo(rh1);
                            d0 = fmaf(qlo.y, bf_hi(rl0), d0); d1 = fmaf(qhi.y, bf_hi(rh0), d1);
                            d2 = fmaf(qlo.w, bf_hi(rl1), d2); d3 = fmaf(qhi.w, bf_hi(rh1), d3);
                            dot = (d0 + d1) + (d2 + d3);
                        }
                        int4 v[RPW];
#pragma unroll
                        for (int r = 0; r < RPW; r++) v[r] = lds128(slot + OFF_V + (row0 + r) * 512 + lane * 16);
                        constexpr int LPR = 32 / RPW;
                        const int myrow = row0 + lane / LPR;
                        const uint32_t vsb = lds16(slot + OFF_VS + myrow * 4 + (lane & 1) * 2);
                        const uint32_t vzb = lds16(slot + OFF_VZ + myrow * 4 + (lane & 1) * 2);
                        const float vsc = __uint_as_float(vsb << 16), vzc = __uint_as_float(vzb << 16);
                        __syncwarp();
                        if (lane == 0) mbar_arrive(smem_u32(&s_empty[s]));
                        if (++s == NST) { s = 0; ph ^= 1; }
                        float t = dot + __shfl_xor_sync(0xffffffffu, dot, 8);
                        t += __shfl_xor_sync(0xffffffffu, t, 4);
                        t += __shfl_xor_sync(0xffffffffu, t, 2);
                        t += __shfl_xor_sync(0xffffffffu, t, 1);
                        const float lg = bf_round(bf_round(t) * 0.08838834764831845f);
                        if (meta >> 16) {
                            if ((lane & (LPR - 1)) < 2)
                                asm volatile("{ .reg .b64 t; mov.b64 t, {%1, %2}; st.relaxed.gpu.global.b64 [%0], t; }"
                                             ::"l"(sc->row + (qh * 2 + (lane & 1)) * R + ((meta >> 16) - 1) * P + myrow),
                                             "r"(__float_as_uint(lg) | tag), "r"(vsb << 16 | vzb) : "memory");
                            continue;
                        }
                        const float mn = fmaxf(m, fmaxf(lg, __shfl_xor_sync(0xffffffffu, lg, 16)));
                        const float alpha = exp_diff(m, mn);
                        const float p = exp_diff(lg, mn);
                        m = mn;
                        const float c = p * vsc;
                        lsum = fmaf(lsum, alpha, p);
                        zsum = fmaf(zsum, alpha, c * vzc);
                        acc0 *= alpha; acc1 *= alpha; acc2 *= alpha; acc3 *= alpha;
#pragma unroll
                        for (int r = 0; r < RPW; r++) {
                            const float cr = __shfl_sync(0xffffffffu, c, LPR * r + hw);
                            acc0 = fmaf(cr, (float)v[r].x, acc0);
                            acc1 = fmaf(cr, (float)v[r].y, acc1);
                            acc2 = fmaf(cr, (float)v[r].z, acc2);
                            acc3 = fmaf(cr, (float)v[r].w, acc3);
                        }
                    } while (nh == cur);

                    float* red = reinterpret_cast<float*>(smem + OFF_RED) + (nflush & 1) * NCW * RED_STRIDE;
                    float l = lsum + __shfl_xor_sync(0xffffffffu, lsum, 16);
                    float z = zsum + __shfl_xor_sync(0xffffffffu, zsum, 16);
                    z = __shfl_sync(0xffffffffu, z, hw);
                    *reinterpret_cast<float4*>(red + cw * RED_STRIDE + 4 * lane) = make_float4(acc0 - z, acc1 - z, acc2 - z, acc3 - z);
                    if (lane == 0) *reinterpret_cast<float2*>(red + cw * RED_STRIDE + D) = make_float2(m, l);
                    asm volatile("bar.sync 1, %0;" ::"n"(NCW * 32) : "memory");
                    if (cw == (nflush & (NCW - 1))) {
                        float2 ml[NCW]; float M = NEG_INF;
#pragma unroll
                        for (int w = 0; w < NCW; w++) { ml[w] = *reinterpret_cast<const float2*>(red + w * RED_STRIDE + D); M = fmaxf(M, ml[w].x); }
                        float4 a = make_float4(0, 0, 0, 0); float L = 0.f;
#pragma unroll
                        for (int w = 0; w < NCW; w++) {
                            const float e = exp_diff(ml[w].x, M);
                            const float4 t = *reinterpret_cast<const float4*>(red + w * RED_STRIDE + 4 * lane);
                            a.x += e * t.x; a.y += e * t.y; a.z += e * t.z; a.w += e * t.w;
                            L += e * ml[w].y;
                        }
                        publish(sc, cur, lane, a, M, L, tag);
                        for (int e = cur + 1; e < nh; e++) publish(sc, e, lane, make_float4(0, 0, 0, 0), NEG_INF, 0.f, tag);
                        if (lane == 0) s_flushed = nh;
                    }
                    nflush++;
                    if (nh >= H) break;
                    cur = nh;
                }
            }
            uint32_t wph = 0;
#pragma unroll 1
            for (int o = blockIdx.x; o < NOWN; o += nct) {
                float o0 = 0.f, o1 = 0.f;
                if (live) mbar_wait(smem_u32(&s_wbar), wph);
                wph ^= 1;
                uint32_t ta = sbase + OFF_TR + (cw * QW + lane) * 4;
#pragma unroll 1
                for (int t = live ? cw / NHW : NT - 1; t < NT; t += NQ) {
                    int4 c[HROWS / 4];
#pragma unroll
                    for (int k = 0; k < HROWS / 4; k++) c[k] = lds128(sbase + OFF_W + (t * TROWS + (cw & (NHW - 1)) * HROWS + 4 * k) * 4);
                    const uint32_t ts = (s + t / 2) % NST;
                    uint32_t va = sbase + ts * SLOT + (t & 1) * T_BYTES + ((cw & (NHW - 1)) * HROWS * QW + lane) * 4, eb = smem_u32(&s_empty[ts]);
                    asm volatile("" : "+r"(va), "+r"(eb), "+r"(ta));
                    if (live) mbar_wait(smem_u32(&s_tile[t]), wph ^ 1);
                    int v[HROWS];
#pragma unroll
                    for (int k = 0; k < HROWS; k++) v[k] = lds32(va + k * QW * 4);
#pragma unroll
                    for (int k = 0; k < HROWS / 4; k++) {
                        o0 = fmaf(__int_as_float(c[k].x), (float)v[4 * k], o0);
                        o1 = fmaf(__int_as_float(c[k].y), (float)v[4 * k + 1], o1);
                        o0 = fmaf(__int_as_float(c[k].z), (float)v[4 * k + 2], o0);
                        o1 = fmaf(__int_as_float(c[k].w), (float)v[4 * k + 3], o1);
                    }
                    if (t + 2 * NST < NT || o + nct < NOWN) {
                        __syncwarp();
                        if (lane == 0 && live) mbar_arrive(eb);
                    }
                }
                asm volatile("{ .reg .pred p; setp.ne.u32 p, %0, 0; st.shared.f32 [%2], %3; @p bar.arrive 4, %1; }"
                             ::"r"(live), "n"((1 + NCW) * 32), "r"(ta), "f"(o0 + o1) : "memory");
                if (live) s = (s + NT / 2) % NST;
            }
            if (live) break;
        }
    }
}

}

extern "C" void kernel_launch(void* const* d_in, const int* in_sizes, int n_in, void* d_out, int out_size) {
    typedef CUresult (*EncodeFn)(CUtensorMap*, CUtensorMapDataType, cuuint32_t, void*, const cuuint64_t*, const cuuint64_t*,
                                 const cuuint32_t*, const cuuint32_t*, CUtensorMapInterleave, CUtensorMapSwizzle,
                                 CUtensorMapL2promotion, CUtensorMapFloatOOBfill);
    static int nsm = 0;
    static EncodeFn encode = nullptr;
    static Scratch* sc = nullptr;
    if (nsm == 0) {
        int dev = 0;
        cudaGetDevice(&dev);
        cudaDeviceGetAttribute(&nsm, cudaDevAttrMultiProcessorCount, dev);
        if (nsm > MAXCTA) nsm = MAXCTA;
        cudaFuncSetAttribute(kv_decode_kernel, cudaFuncAttributeMaxDynamicSharedMemorySize, SMEM_BYTES);
        cudaGetSymbolAddress((void**)&sc, g_scratch);
        cudaDriverEntryPointQueryResult qr;
        cudaGetDriverEntryPoint("cuTensorMapEncodeTiled", (void**)&encode, cudaEnableDefault, &qr);
    }
    CUtensorMap vmap;
    const cuuint64_t gdim[2] = {(cuuint64_t)D, (cuuint64_t)H * S};
    const cuuint64_t gstr[1] = {(cuuint64_t)D * 4};
    const cuuint32_t box[2] = {(cuuint32_t)QW, (cuuint32_t)TROWS};
    const cuuint32_t estr[2] = {1, 1};
    encode(&vmap, CU_TENSOR_MAP_DATA_TYPE_INT32, 2, d_in[4], gdim, gstr, box, estr, CU_TENSOR_MAP_INTERLEAVE_NONE,
           CU_TENSOR_MAP_SWIZZLE_NONE, CU_TENSOR_MAP_L2_PROMOTION_NONE, CU_TENSOR_MAP_FLOAT_OOB_FILL_NONE);
    kv_decode_kernel<<<nsm, NTHREADS, SMEM_BYTES>>>(
        (const int*)d_in[1], (const int*)d_in[4], (const __nv_bfloat16*)d_in[9], (const __nv_bfloat16*)d_in[10],
        sc->ticket, nsm,
        (const __nv_bfloat16*)d_in[2], (const __nv_bfloat16*)d_in[3], (const __nv_bfloat16*)d_in[5],
        (const __nv_bfloat16*)d_in[6], (const __nv_bfloat16*)d_in[0], (const __nv_bfloat16*)d_in[7],
        (const __nv_bfloat16*)d_in[8], (__nv_bfloat16*)d_out, sc, vmap);
}
```
